```python
import torch

def _softmax(x, axis=-1):
    return torch.softmax(x, dim=axis)
def _gelu(x):
    return torch.nn.functional.gelu(x, approximate="tanh")
def _silu(x):
    return torch.nn.functional.silu(x)
def _sigmoid(x):
    return torch.sigmoid(x)
def _layernorm(x, axis=-1, eps=1e-5):
    m = x.mean(dim=axis, keepdim=True)
    v = x.var(dim=axis, keepdim=True, unbiased=False)
    return (x - m) / torch.sqrt(v + eps)
def _scatter_add(tgt, idx, src, axis=0):
    return tgt.clone().index_add_(axis, idx, src)
def _segment_sum(src, seg, n):
    out = torch.zeros((n,) + src.shape[1:], dtype=src.dtype)
    return out.index_add_(0, seg, src)
def _pad(x, pw):
    flat = tuple(v for pair in reversed(pw) for v in pair)
    return torch.nn.functional.pad(x, flat)

kernel_name = 'standalone__deep_cross_xdeepfm__recsys'

def setup_inputs():

    _w = (lambda a: (lambda t: t.to(torch.bfloat16) if t.is_floating_point() else t)(torch.as_tensor(a)))
    B, F, D, L = 4096, 26, 64, 3
    V = min(1000000, 100000)
    Din = F * D
    return {
        "idx": _w((lambda lo, hi, *s: torch.randint(lo, hi, s))(0, V, B, F).to(torch.int64)),
        "table": _w((lambda *s: torch.randn(*s, dtype=torch.bfloat16) * 0.8)(V, D)),
        "ws_cin": _w((lambda *s: torch.randn(*s, dtype=torch.bfloat16) * 0.2)(L, F, F, F) * (1.0 / F)),
        "w_cin_out": _w((lambda *s: torch.randn(*s, dtype=torch.bfloat16) * 0.2)(L * F) * ((L * F) ** -0.5)),
        "w_dnn1": _w((lambda *s: torch.randn(*s, dtype=torch.bfloat16) * 0.8)(Din, Din) * (Din ** -0.5)),
        "b_dnn1": _w((lambda *s: torch.randn(*s, dtype=torch.bfloat16) * 1.6)(Din) * 0.1),
        "w_dnn2": _w((lambda *s: torch.randn(*s, dtype=torch.bfloat16) * 0.2)(Din) * (Din ** -0.5)),
        "b_out": _w((lambda *s: torch.randn(*s, dtype=torch.bfloat16) * 0.2)(1)),
    }

def reference(idx, table, ws_cin, w_cin_out, w_dnn1, b_dnn1, w_dnn2, b_out):
    x0 = table[idx]
    B = x0.shape[0]
    L = ws_cin.shape[0]
    xk = x0
    pooled = []
    for l in range(L):
        xk = torch.einsum('bid,bjd,hij->bhd', xk, x0, ws_cin[l])
        pooled.append(xk.sum(axis=-1))
    p_plus = torch.stack(pooled, axis=1).reshape(B, -1)
    logit_cin = p_plus @ w_cin_out
    h = x0.reshape(B, -1)
    h = _gelu(h @ w_dnn1 + b_dnn1)
    logit_dnn = h @ w_dnn2
    return logit_cin + logit_dnn + b_out
```

```cpp
#include <cuda_runtime.h>
#include <cuda_bf16.h>
#include <cuda.h>
#include <stdint.h>

__device__ __forceinline__ void wgmma_ss_n256(float (&d)[96], float (&e)[32], uint64_t descA, uint64_t descB, int scaleD) {
  asm volatile("{\n.reg .pred p;\nsetp.ne.b32 p, %130, 0;\n"
      "wgmma.mma_async.sync.aligned.m64n256k16.f32.bf16.bf16 {"
      "%0, %1, %2, %3, %4, %5, %6, %7, %8, %9, %10, %11, %12, %13, %14, %15,"
      "%16, %17, %18, %19, %20, %21, %22, %23, %24, %25, %26, %27, %28, %29, %30, %31,"
      "%32, %33, %34, %35, %36, %37, %38, %39, %40, %41, %42, %43, %44, %45, %46, %47,"
      "%48, %49, %50, %51, %52, %53, %54, %55, %56, %57, %58, %59, %60, %61, %62, %63,"
      "%64, %65, %66, %67, %68, %69, %70, %71, %72, %73, %74, %75, %76, %77, %78, %79,"
      "%80, %81, %82, %83, %84, %85, %86, %87, %88, %89, %90, %91, %92, %93, %94, %95,"
      "%96, %97, %98, %99, %100, %101, %102, %103, %104, %105, %106, %107, %108, %109, %110, %111,"
      "%112, %113, %114, %115, %116, %117, %118, %119, %120, %121, %122, %123, %124, %125, %126, %127"
      "}, %128, %129, p, 1, 1, 0, 1;\n}\n"
      : "+f"(d[0]), "+f"(d[1]), "+f"(d[2]), "+f"(d[3]), "+f"(d[4]), "+f"(d[5]), "+f"(d[6]), "+f"(d[7]),
        "+f"(d[8]), "+f"(d[9]), "+f"(d[10]), "+f"(d[11]), "+f"(d[12]), "+f"(d[13]), "+f"(d[14]), "+f"(d[15]),
        "+f"(d[16]), "+f"(d[17]), "+f"(d[18]), "+f"(d[19]), "+f"(d[20]), "+f"(d[21]), "+f"(d[22]), "+f"(d[23]),
        "+f"(d[24]), "+f"(d[25]), "+f"(d[26]), "+f"(d[27]), "+f"(d[28]), "+f"(d[29]), "+f"(d[30]), "+f"(d[31]),
        "+f"(d[32]), "+f"(d[33]), "+f"(d[34]), "+f"(d[35]), "+f"(d[36]), "+f"(d[37]), "+f"(d[38]), "+f"(d[39]),
        "+f"(d[40]), "+f"(d[41]), "+f"(d[42]), "+f"(d[43]), "+f"(d[44]), "+f"(d[45]), "+f"(d[46]), "+f"(d[47]),
        "+f"(d[48]), "+f"(d[49]), "+f"(d[50]), "+f"(d[51]), "+f"(d[52]), "+f"(d[53]), "+f"(d[54]), "+f"(d[55]),
        "+f"(d[56]), "+f"(d[57]), "+f"(d[58]), "+f"(d[59]), "+f"(d[60]), "+f"(d[61]), "+f"(d[62]), "+f"(d[63]),
        "+f"(d[64]), "+f"(d[65]), "+f"(d[66]), "+f"(d[67]), "+f"(d[68]), "+f"(d[69]), "+f"(d[70]), "+f"(d[71]),
        "+f"(d[72]), "+f"(d[73]), "+f"(d[74]), "+f"(d[75]), "+f"(d[76]), "+f"(d[77]), "+f"(d[78]), "+f"(d[79]),
        "+f"(d[80]), "+f"(d[81]), "+f"(d[82]), "+f"(d[83]), "+f"(d[84]), "+f"(d[85]), "+f"(d[86]), "+f"(d[87]),
        "+f"(d[88]), "+f"(d[89]), "+f"(d[90]), "+f"(d[91]), "+f"(d[92]), "+f"(d[93]), "+f"(d[94]), "+f"(d[95]),
        "+f"(e[0]), "+f"(e[1]), "+f"(e[2]), "+f"(e[3]), "+f"(e[4]), "+f"(e[5]), "+f"(e[6]), "+f"(e[7]),
        "+f"(e[8]), "+f"(e[9]), "+f"(e[10]), "+f"(e[11]), "+f"(e[12]), "+f"(e[13]), "+f"(e[14]), "+f"(e[15]),
        "+f"(e[16]), "+f"(e[17]), "+f"(e[18]), "+f"(e[19]), "+f"(e[20]), "+f"(e[21]), "+f"(e[22]), "+f"(e[23]),
        "+f"(e[24]), "+f"(e[25]), "+f"(e[26]), "+f"(e[27]), "+f"(e[28]), "+f"(e[29]), "+f"(e[30]), "+f"(e[31])
      : "l"(descA), "l"(descB), "r"(scaleD));
}
__device__ __forceinline__ void wgmma_ss_n192(float (&d)[96], uint64_t descA, uint64_t descB, int scaleD) {
  asm volatile("{\n.reg .pred p;\nsetp.ne.b32 p, %98, 0;\n"
      "wgmma.mma_async.sync.aligned.m64n192k16.f32.bf16.bf16 {"
      "%0, %1, %2, %3, %4, %5, %6, %7, %8, %9, %10, %11, %12, %13, %14, %15,"
      "%16, %17, %18, %19, %20, %21, %22, %23, %24, %25, %26, %27, %28, %29, %30, %31,"
      "%32, %33, %34, %35, %36, %37, %38, %39, %40, %41, %42, %43, %44, %45, %46, %47,"
      "%48, %49, %50, %51, %52, %53, %54, %55, %56, %57, %58, %59, %60, %61, %62, %63,"
      "%64, %65, %66, %67, %68, %69, %70, %71, %72, %73, %74, %75, %76, %77, %78, %79,"
      "%80, %81, %82, %83, %84, %85, %86, %87, %88, %89, %90, %91, %92, %93, %94, %95"
      "}, %96, %97, p, 1, 1, 0, 1;\n}\n"
      : "+f"(d[0]), "+f"(d[1]), "+f"(d[2]), "+f"(d[3]), "+f"(d[4]), "+f"(d[5]), "+f"(d[6]), "+f"(d[7]),
        "+f"(d[8]), "+f"(d[9]), "+f"(d[10]), "+f"(d[11]), "+f"(d[12]), "+f"(d[13]), "+f"(d[14]), "+f"(d[15]),
        "+f"(d[16]), "+f"(d[17]), "+f"(d[18]), "+f"(d[19]), "+f"(d[20]), "+f"(d[21]), "+f"(d[22]), "+f"(d[23]),
        "+f"(d[24]), "+f"(d[25]), "+f"(d[26]), "+f"(d[27]), "+f"(d[28]), "+f"(d[29]), "+f"(d[30]), "+f"(d[31]),
        "+f"(d[32]), "+f"(d[33]), "+f"(d[34]), "+f"(d[35]), "+f"(d[36]), "+f"(d[37]), "+f"(d[38]), "+f"(d[39]),
        "+f"(d[40]), "+f"(d[41]), "+f"(d[42]), "+f"(d[43]), "+f"(d[44]), "+f"(d[45]), "+f"(d[46]), "+f"(d[47]),
        "+f"(d[48]), "+f"(d[49]), "+f"(d[50]), "+f"(d[51]), "+f"(d[52]), "+f"(d[53]), "+f"(d[54]), "+f"(d[55]),
        "+f"(d[56]), "+f"(d[57]), "+f"(d[58]), "+f"(d[59]), "+f"(d[60]), "+f"(d[61]), "+f"(d[62]), "+f"(d[63]),
        "+f"(d[64]), "+f"(d[65]), "+f"(d[66]), "+f"(d[67]), "+f"(d[68]), "+f"(d[69]), "+f"(d[70]), "+f"(d[71]),
        "+f"(d[72]), "+f"(d[73]), "+f"(d[74]), "+f"(d[75]), "+f"(d[76]), "+f"(d[77]), "+f"(d[78]), "+f"(d[79]),
        "+f"(d[80]), "+f"(d[81]), "+f"(d[82]), "+f"(d[83]), "+f"(d[84]), "+f"(d[85]), "+f"(d[86]), "+f"(d[87]),
        "+f"(d[88]), "+f"(d[89]), "+f"(d[90]), "+f"(d[91]), "+f"(d[92]), "+f"(d[93]), "+f"(d[94]), "+f"(d[95])
      : "l"(descA), "l"(descB), "r"(scaleD));
}
template <unsigned long long DESC, int SCALE>
__device__ __forceinline__ void wgmma_rs_n56(float (&d)[28], uint32_t a0, uint32_t a1, uint32_t a2, uint32_t a3) {
  asm volatile("{\n.reg .b64 desc;\nmov.b64 desc, %32;\n"
      "wgmma.mma_async.sync.aligned.m64n56k16.f32.bf16.bf16 {"
      "%0, %1, %2, %3, %4, %5, %6, %7, %8, %9, %10, %11, %12, %13, %14, %15,"
      "%16, %17, %18, %19, %20, %21, %22, %23, %24, %25, %26, %27"
      "}, {%28, %29, %30, %31}, desc, %33, 1, 1, 0;\n}\n"
      : "+f"(d[0]), "+f"(d[1]), "+f"(d[2]), "+f"(d[3]), "+f"(d[4]), "+f"(d[5]), "+f"(d[6]), "+f"(d[7]),
        "+f"(d[8]), "+f"(d[9]), "+f"(d[10]), "+f"(d[11]), "+f"(d[12]), "+f"(d[13]), "+f"(d[14]), "+f"(d[15]),
        "+f"(d[16]), "+f"(d[17]), "+f"(d[18]), "+f"(d[19]), "+f"(d[20]), "+f"(d[21]), "+f"(d[22]), "+f"(d[23]),
        "+f"(d[24]), "+f"(d[25]), "+f"(d[26]), "+f"(d[27])
      : "r"(a0), "r"(a1), "r"(a2), "r"(a3), "n"(DESC), "n"(SCALE));
}
template <unsigned long long DESC, int SCALE>
__device__ __forceinline__ void wgmma_rs_n32(float (&d)[28], uint32_t a0, uint32_t a1, uint32_t a2, uint32_t a3) {
  asm volatile("{\n.reg .b64 desc;\nmov.b64 desc, %20;\n"
      "wgmma.mma_async.sync.aligned.m64n32k16.f32.bf16.bf16 {"
      "%0, %1, %2, %3, %4, %5, %6, %7, %8, %9, %10, %11, %12, %13, %14, %15"
      "}, {%16, %17, %18, %19}, desc, %21, 1, 1, 0;\n}\n"
      : "+f"(d[0]), "+f"(d[1]), "+f"(d[2]), "+f"(d[3]), "+f"(d[4]), "+f"(d[5]), "+f"(d[6]), "+f"(d[7]),
        "+f"(d[8]), "+f"(d[9]), "+f"(d[10]), "+f"(d[11]), "+f"(d[12]), "+f"(d[13]), "+f"(d[14]), "+f"(d[15])
      : "r"(a0), "r"(a1), "r"(a2), "r"(a3), "n"(DESC), "n"(SCALE));
}

constexpr int NB = 4096, NF = 26, DIN = 1664;
constexpr int NGEMM = 128, NEXTRA = 4, GRID = NGEMM + NEXTRA;
constexpr int NC_EXTRA = 84;
constexpr int NC_WG0 = 16;
constexpr int HK = 4;
constexpr int PE0 = 9;
constexpr int WD = 2;
constexpr int GI = 3;
constexpr int PE1 = 4;
constexpr int PE2 = 8;
constexpr int PS2 = 6;
constexpr int POLL = 400;
constexpr int BGN = 1;
constexpr int PREG = 48;
constexpr int PS = 6;
constexpr int RB = 4;
constexpr int NC_GEMM = 29, NBIG = NB - NGEMM * NC_GEMM - NEXTRA * NC_EXTRA;
static_assert(NBIG >= 0 && NBIG <= NGEMM && NC_EXTRA % 4 == 0 && NC_EXTRA <= 96, "split");
constexpr int CW_MAIN = 22 * 1792, CW_LIN = 2 * 1024, CW_BYTES = CW_MAIN + CW_LIN;
constexpr int XSLOT = 4096;

constexpr int UNIT = 8192, FS = 18;
constexpr int U_W = 6, U_XB = 18, U_SP = 24;
constexpr int CW_CUT = 9;
constexpr int OFF_CW = 0, OFF_CW2 = 6 * UNIT, OFF_CWL = 9 * UNIT;
constexpr int CROW = 528;
constexpr int OFF_PARK = 10 * UNIT, OFF_PARK2 = 24 * UNIT;
constexpr int OFF_RS0 = OFF_CWL + CW_LIN, OFF_RS1 = OFF_CWL - 1024;
constexpr int OFF_GIDX = 26 * UNIT;
constexpr int OFF_TIDX = OFF_GIDX + 128 * NF * 4 - 8 * 64 * 4;
constexpr int OFF_CIDX = OFF_GIDX + 128 * NF * 4;
constexpr int OFF_EPI = OFF_CIDX + 32 * 8 * 4;
constexpr int OFF_DNN = OFF_EPI + 128 * 16;
constexpr int OFF_BAR = OFF_DNN + 112 * 8;
constexpr int SMEM_BYTES = OFF_BAR + 50 * 8;
static_assert(CW_CUT * 1792 <= 2 * UNIT && (22 - CW_CUT) * 1792 <= 3 * UNIT , "smem");
constexpr uint32_t SMEM_BASE = 1024;
static_assert(SMEM_BYTES <= 232448, "smem");
static_assert(OFF_EPI % 16 == 0 && OFF_BAR % 8 == 0, "align");
constexpr int XOFF_W3 = 0, XOFF_W2 = 35152, XOFF_W1 = 70304, XOFF_M = XOFF_W1 + 8 * 1352, XOFF_S = XOFF_M + 32 * 40 * 4,
              XOFF_SLOT = 10 * UNIT, XOFF_CIN0 = 2 * UNIT, XOFF_CIN1 = 18 * UNIT, XOFF_CIDX = 22 * UNIT,
              XOFF_BAR = 24 * UNIT, NPAIR = NC_EXTRA / 4;
static_assert(XOFF_S + 14 * 3136 <= 21 * UNIT && 48 * CROW <= 4 * UNIT, "smem");

constexpr int BAR_PARK = 7,
              BAR_FULL = 8,
              BAR_EV = 16,
              BAR_CW = 24,
              BAR_GIDX = 25,
              BAR_X0 = 26,
              BAR_W0 = 27,
              BAR_DNN = 28,
              BAR_T = 29,
              BAR_GDONE = 30,
              BAR_EPOCH = 31,
              BAR_CFULL = 32,
              BAR_C0 = 48;
constexpr int EV_CW = 29, EV_SLOT = 30, EV_END = 33;
__device__ __forceinline__ uint32_t ev_bar(uint32_t bars, int e) { return bars + 8 * (BAR_EV + (e & 7)); }
__device__ __forceinline__ uint32_t ev_par(int e) { return (e >> 3) & 1; }
constexpr unsigned long long STAGES = 0xb4b4924924924ull;
__host__ __device__ constexpr int b_x(int t) { return ((0xb2c1430bu >> (4 * t)) & 15) * 2; }
__host__ __device__ constexpr int b_w(int t) { return (0x0d0a120eu >> (8 * (t & 3))) & 31; }
__host__ __device__ constexpr int b_ws(int t) { return (t & 3) == 3 ? 4 : 1; }

struct Scratch {
  uint4 cw[CW_BYTES / 16];
  uint2 part[8 * NB];
  unsigned epoch[GRID];
  unsigned foldflag;
};
__device__ __align__(128) Scratch g_scratch;
__device__ __align__(1024) __nv_bfloat16 g_x0[NB * FS * 64];
struct GPtr { Scratch* s; const uint4* tab; uint32_t zero; };

__device__ __forceinline__ void wg_fence() { asm volatile("wgmma.fence.sync.aligned;" ::: "memory"); }
__device__ __forceinline__ void wg_commit() { asm volatile("wgmma.commit_group.sync.aligned;" ::: "memory"); }
template <int N> __device__ __forceinline__ void wg_wait() { asm volatile("wgmma.wait_group.sync.aligned %0;" ::"n"(N) : "memory"); }
__device__ __forceinline__ uint64_t mkdesc(uint32_t addr, uint32_t lbo, uint32_t sbo, uint32_t swz) {
  return (uint64_t)((addr & 0x3FFFF) >> 4) | ((uint64_t)(lbo >> 4) << 16) | ((uint64_t)(sbo >> 4) << 32) | ((uint64_t)swz << 62);
}
__device__ __forceinline__ bool elect1() {
  uint32_t p; asm volatile("{\n.reg .pred p;\nelect.sync _|p, 0xffffffff;\nselp.b32 %0, 1, 0, p;\n}" : "=r"(p)); return p;
}
__device__ __forceinline__ int fresh(int v) { asm volatile("" : "+r"(v)); return v; }
__device__ __forceinline__ void mbar_init(uint32_t bar, uint32_t cnt) { asm volatile("mbarrier.init.shared::cta.b64 [%0], %1;" ::"r"(bar), "r"(cnt) : "memory"); }
__device__ __forceinline__ void mbar_arrive(uint32_t bar) { asm volatile("mbarrier.arrive.shared::cta.b64 _, [%0];" ::"r"(bar) : "memory"); }
__device__ __forceinline__ void mbar_arrive_cta(uint32_t bar, uint32_t cta) {
  asm volatile("{\n.reg .b32 r;\nmapa.shared::cluster.u32 r, %0, %1;\nmbarrier.arrive.shared::cluster.b64 _, [r];\n}" ::"r"(bar), "r"(cta) : "memory");
}
__device__ __forceinline__ void mbar_expect_tx(uint32_t bar, uint32_t bytes) { asm volatile("mbarrier.arrive.expect_tx.shared::cta.b64 _, [%0], %1;" ::"r"(bar), "r"(bytes) : "memory"); }
__device__ __forceinline__ void mbar_wait(uint32_t bar, uint32_t parity) {
  asm volatile("{\n.reg .pred p;\n.reg .u32 n;\n"
               "mbarrier.try_wait.parity.shared::cta.b64 p, [%0], %1;\n"
               "@p bra DONE;\n"
               "mov.u32 n, 0;\nLAB_WAIT:\n"
               "mbarrier.try_wait.parity.shared::cta.b64 p, [%0], %1;\n"
               "@p bra DONE;\n"
               "add.u32 n, n, 1;\n"
               "setp.lt.u32 p, n, 400000;\n"
               "@p bra LAB_WAIT;\n"
               "DONE:\n}" ::"r"(bar), "r"(parity) : "memory");
}
__device__ __forceinline__ void flag_wait(const unsigned* p, unsigned target, unsigned sleep_ns) {
  asm volatile("{\n.reg .pred p;\n.reg .u32 n, v;\nmov.u32 n, 0;\nLAB_WAIT:\n"
               "ld.acquire.gpu.global.u32 v, [%0];\n"
               "sub.u32 v, v, %1;\n"
               "setp.ge.s32 p, v, 0;\n"
               "@p bra DONE;\n"
               "nanosleep.u32 %2;\n"
               "add.u32 n, n, 1;\n"
               "setp.lt.u32 p, n, 400000;\n"
               "@p bra LAB_WAIT;\n"
               "DONE:\n}" ::"l"(p), "r"(target), "r"(sleep_ns) : "memory");
}
__device__ __forceinline__ void put_tagged(uint2* p, float v, unsigned tag) {
  asm volatile("st.relaxed.gpu.global.v2.b32 [%0], {%1, %2};" ::"l"(p), "r"(__float_as_uint(v)), "r"(tag) : "memory");
}
__device__ __forceinline__ void flag_add(unsigned* p) { asm volatile("red.release.gpu.global.add.u32 [%0], 1;" ::"l"(p) : "memory"); }
__device__ __forceinline__ void tma_load(uint32_t dst, const CUtensorMap* tm, int c0, int c1, uint32_t bar) {
  asm volatile("cp.async.bulk.tensor.2d.shared::cluster.global.mbarrier::complete_tx::bytes [%0], [%1, {%3, %4}], [%2];"
               ::"r"(dst), "l"(tm), "r"(bar), "r"(c0), "r"(c1) : "memory");
}
__device__ __forceinline__ void tma_row_mc(uint32_t dst, const CUtensorMap* tm, int row, uint32_t bar) {
  asm volatile("cp.async.bulk.tensor.2d.shared::cluster.global.mbarrier::complete_tx::bytes.multicast::cluster [%0], [%1, {%3, %4}], [%2], %5;"
               ::"r"(dst), "l"(tm), "r"(bar), "r"(0), "r"(row), "h"((uint16_t)3));
}
__device__ __forceinline__ void tma_row(uint32_t dst, const CUtensorMap* tm, int row, uint32_t bar) {
  asm volatile("cp.async.bulk.tensor.2d.shared::cluster.global.mbarrier::complete_tx::bytes [%0], [%1, {%3, %4}], [%2];"
               ::"r"(dst), "l"(tm), "r"(bar), "r"(0), "r"(row));
}
__device__ __forceinline__ void tma_store(const CUtensorMap* tm, int c0, int c1, uint32_t src) {
  asm volatile("cp.async.bulk.tensor.2d.global.shared::cta.bulk_group [%0, {%1, %2}], [%3];\ncp.async.bulk.commit_group;"
               ::"l"(tm), "r"(c0), "r"(c1), "r"(src) : "memory");
}
template <int N> __device__ __forceinline__ void store_read() { asm volatile("cp.async.bulk.wait_group.read %0;" ::"n"(N) : "memory"); }
__device__ __forceinline__ void bulk_load(uint32_t dst, const void* src, uint32_t bytes, uint32_t bar) {
  asm volatile("cp.async.bulk.shared::cluster.global.mbarrier::complete_tx::bytes [%0], [%1], %2, [%3];"
               ::"r"(dst), "l"(src), "r"(bytes), "r"(bar));
}
__device__ __forceinline__ void l2_prefetch(const void* src, uint32_t bytes) {
  asm volatile("cp.async.bulk.prefetch.L2.global [%0], %1;" ::"l"(src), "r"(bytes));
}
__device__ __forceinline__ void w_prefetch(const __nv_bfloat16* w1, int f, int cta, int piece) {
  l2_prefetch(w1 + (f * 64 + (cta >> 3) * 4 + (cta & 1) * 2 + (piece & 1)) * DIN + (piece < 2 ? (cta & 6) * 192 : 1536 + (cta & 4) * 16),
              piece < 2 ? 768 : 128);
}
__device__ __forceinline__ void cpasync16(uint32_t dst, const void* src) {
  asm volatile("cp.async.cg.shared.global [%0], [%1], 16;" ::"r"(dst), "l"(src) : "memory");
}
template <int ID, int N> __device__ __forceinline__ void bar_sync() { asm volatile("bar.sync %0, %1;" ::"n"(ID), "n"(N) : "memory"); }
template <int ID, int N> __device__ __forceinline__ void bar_arrive() { asm volatile("bar.arrive %0, %1;" ::"n"(ID), "n"(N) : "memory"); }
__device__ __forceinline__ void ldsm4t(uint32_t& a, uint32_t& b, uint32_t& c, uint32_t& d, uint32_t addr) {
  asm volatile("ldmatrix.sync.aligned.m8n8.x4.trans.shared.b16 {%0,%1,%2,%3}, [%4];" : "=r"(a), "=r"(b), "=r"(c), "=r"(d) : "r"(addr) : "memory");
}
__device__ __forceinline__ int lds32(uint32_t addr) { int v; asm volatile("ld.shared.b32 %0, [%1];" : "=r"(v) : "r"(addr)); return v; }
__device__ __forceinline__ int2 lds64(uint32_t addr) { int2 v; asm volatile("ld.shared.v2.b32 {%0,%1}, [%2];" : "=r"(v.x), "=r"(v.y) : "r"(addr)); return v; }
__device__ __forceinline__ int4 lds128(uint32_t addr) {
  int4 v; asm volatile("ld.shared.v4.b32 {%0,%1,%2,%3}, [%4];" : "=r"(v.x), "=r"(v.y), "=r"(v.z), "=r"(v.w) : "r"(addr)); return v;
}
__device__ __forceinline__ float4 lds128f(uint32_t addr) {
  float4 v; asm volatile("ld.shared.v4.f32 {%0,%1,%2,%3}, [%4];" : "=f"(v.x), "=f"(v.y), "=f"(v.z), "=f"(v.w) : "r"(addr) : "memory"); return v;
}
__device__ __forceinline__ void sts32f(uint32_t addr, float v) { asm volatile("st.shared.f32 [%0], %1;" ::"r"(addr), "f"(v) : "memory"); }
__device__ __forceinline__ float bf_lo(uint32_t v) { return __uint_as_float(v << 16); }
__device__ __forceinline__ float bf_hi(uint32_t v) { return __uint_as_float(v & 0xffff0000u); }
__device__ __forceinline__ float bf2f(__nv_bfloat16 v) { return __bfloat162float(v); }

__device__ __forceinline__ uint32_t mul2(uint32_t a, uint32_t b) {
  uint32_t r; asm volatile("mul.rn.bf16x2 %0, %1, %2;" : "=r"(r) : "r"(a), "r"(b)); return r;
}
__device__ __forceinline__ uint32_t mul2lo(uint32_t a, uint32_t b) {
  uint32_t r;
  asm volatile("{\n.reg .b16 l, h;\n.reg .b32 t;\nmov.b32 {l, h}, %2;\nmov.b32 t, {l, l};\nmul.rn.bf16x2 %0, %1, t;\n}" : "=r"(r) : "r"(a), "r"(b));
  return r;
}
__device__ __forceinline__ uint32_t mul2hi(uint32_t a, uint32_t b) {
  uint32_t r;
  asm volatile("{\n.reg .b16 l, h;\n.reg .b32 t;\nmov.b32 {l, h}, %2;\nmov.b32 t, {h, h};\nmul.rn.bf16x2 %0, %1, t;\n}" : "=r"(r) : "r"(a), "r"(b));
  return r;
}

__host__ __device__ constexpr int xfield(int r, int e, int c) {
  return r == 9 ? 24 + e : 8 * (r / 3) + 2 * (((r % 3) + c) & 3) + (((r % 3) == 2 && c >= 2) ? 1 - e : e);
}
__host__ __device__ constexpr int blk_a(int b) { return b < 12 ? 3 * (b / 8) + ((b & 3) == 3) : (b < 15 ? 3 * (b - 12) : 3 * (b - 15)); }
__host__ __device__ constexpr int blk_b(int b) { return b < 12 ? 3 * (b < 4 ? 1 : 2) + ((b & 3) == 3 ? 0 : (b & 3)) : (b < 15 ? 3 * (b - 12) + 1 : 9); }
__host__ __device__ constexpr int slot_pq(int u, int e, int c) {
  return u < 36 ? (xfield(blk_a(u >> 1), e, c) | (xfield(blk_b(u >> 1), u & 1, c) << 8))
       : u < 39 ? (xfield(3 * (u - 36), e, c) * 257)
       : u < 42 ? (xfield(3 * (u - 39), e, c) | (xfield(3 * (u - 39) + 2, e, c) << 8))
       : u == 42 ? (xfield(3 * e, 0, c) | (xfield(3 * e, 1, c) << 8))
       : u == 43 ? (e == 0 ? (xfield(6, 0, c) | (xfield(6, 1, c) << 8))
                           : (c == 0 ? 24 * 257 : c == 1 ? 25 * 257 : c == 2 ? (24 | 25 << 8) : 26 * 257))
       : u < 47 ? (xfield(3 * (u - 44), e, c) | (26 << 8))
       : (c == 0 ? ((24 + e) | 26 << 8) : 27 * 257);
}
struct SlotTab { uint32_t v[48 * 8]; };
constexpr SlotTab make_slot_tab() {
  SlotTab t{};
  for (int u = 0; u < 48; u++)
    for (int k = 0; k < 8; k++) {
      const int pq = slot_pq(u, k & 1, k >> 1), p = pq & 255, q = pq >> 8;
      t.v[u * 8 + k] = (uint32_t)((p * 28 + q) * 4) | ((uint32_t)(((p != q && q < 26) ? q * 28 + p : 27 * 28 + 27) * 4) << 16);
    }
  return t;
}
__device__ __align__(16) const SlotTab g_slot_tab = make_slot_tab();

struct CinCtx {
  uint32_t o03, o14, o25, o69, o78, cin, selA, selB;
  bool ones, lead;
  uint32_t so, so2, co, co2, bar, jump, dslot, last;
  bool ring;
};
constexpr unsigned long long CW_DESC = (unsigned long long)((SMEM_BASE + OFF_CW) >> 4) | (8ull << 16) | (16ull << 32);
constexpr unsigned long long CWL_DESC = CW_DESC + (OFF_CWL - OFF_CW) / 16;

template <int U>
__device__ __forceinline__ uint32_t zreg(const uint32_t (&x)[10][2], int h, const CinCtx& c) {
  if constexpr (U < 36) {
    if constexpr (U & 1) return mul2hi(x[blk_a(U >> 1)][h], x[blk_b(U >> 1)][h]);
    else return mul2lo(x[blk_a(U >> 1)][h], x[blk_b(U >> 1)][h]);
  } else if constexpr (U < 39) {
    return mul2(x[3 * (U - 36)][h], x[3 * (U - 36)][h]);
  } else if constexpr (U < 42) {
    return mul2(x[3 * (U - 39)][h], x[3 * (U - 39) + 2][h]);
  } else if constexpr (U == 42) {
    return mul2(__byte_perm(x[0][h], x[3][h], 0x5410), __byte_perm(x[0][h], x[3][h], 0x7632));
  } else {
    const uint32_t f = c.ones ? 0x3f803f80u : x[9][h];
    return mul2(__byte_perm(x[6][h], f, c.selA), __byte_perm(x[6][h], f, c.selB));
  }
}

template <int G>
__device__ __forceinline__ void z_fill(uint32_t (&z)[8], const uint32_t (&x)[10][2], const CinCtx& c) {
  z[0] = zreg<4 * G>(x, 0, c);     z[1] = zreg<4 * G>(x, 1, c);
  z[2] = zreg<4 * G + 1>(x, 0, c); z[3] = zreg<4 * G + 1>(x, 1, c);
  z[4] = zreg<4 * G + 2>(x, 0, c); z[5] = zreg<4 * G + 2>(x, 1, c);
  z[6] = zreg<4 * G + 3>(x, 0, c); z[7] = zreg<4 * G + 3>(x, 1, c);
}
__host__ __device__ constexpr unsigned long long cw_desc(int s) { return CW_DESC + (s < CW_CUT ? s * 1792 : OFF_CW2 - OFF_CW + (s - CW_CUT) * 1792) / 16; }
template <int G>
__device__ __forceinline__ void z_mma(float (&acc)[28], const uint32_t (&z)[8]) {
  wgmma_rs_n56<cw_desc(2 * G), G != 0>(acc, z[0], z[1], z[2], z[3]);
  wgmma_rs_n56<cw_desc(2 * G + 1), 1>(acc, z[4], z[5], z[6], z[7]);
}

__device__ __forceinline__ void cin_finish(const CinCtx& c, float (&acc)[28], uint32_t out) {
#pragma unroll
  for (int i = 0; i < 28; i++) asm volatile("" : "+f"(acc[i]));
  float s0 = acc[12] * acc[13], s1 = acc[14] * acc[15];
#pragma unroll
  for (int i = 0; i < 12; i += 2) {
    s0 = fmaf(acc[i], acc[16 + i], s0);
    s1 = fmaf(acc[i + 1], acc[17 + i], s1);
  }
  sts32f(c.cin + out, s0 + s1);
}

__device__ __forceinline__ void cin_ldsm(const CinCtx& c, uint32_t so, uint32_t (&x)[10][2]) {
  ldsm4t(x[0][0], x[0][1], x[3][0], x[3][1], so + c.o03);
  ldsm4t(x[1][0], x[1][1], x[4][0], x[4][1], so + c.o14);
  ldsm4t(x[2][0], x[2][1], x[5][0], x[5][1], so + c.o25);
  ldsm4t(x[6][0], x[6][1], x[9][0], x[9][1], so + c.o69);
  ldsm4t(x[7][0], x[7][1], x[8][0], x[8][1], so + c.o78);
}
__device__ __forceinline__ void cin_load(const CinCtx& c, int k, bool real, uint32_t (&x)[10][2]) {
  if (k == 0 && real) mbar_wait(c.bar, 0);
  cin_ldsm(c, k ? c.so2 : c.so, x);
  if (k == 1 && c.lead) mbar_arrive(c.bar + 8 * NPAIR);
}
__device__ __forceinline__ void cin_advance(CinCtx& c) {
  const uint32_t d = c.so == c.jump ? c.dslot : 2 * XSLOT;
  c.so += d; c.so2 += d;
  c.co = c.ring ? c.co + 2 * CROW : c.so;
  c.bar += 8;
}
constexpr int CG_WAIT = 2;
constexpr int CG_FIN = 2;
constexpr int CG_HEAD = 3;
constexpr int CG_LIN = 3;
constexpr int CG_LOAD = 5;
constexpr int CG_N = 11;
static_assert(CG_FIN >= CG_WAIT && CG_FIN < CG_HEAD && CG_LOAD >= CG_HEAD && CG_LIN > 0, "CIN schedule");
template <int G, int GEND, typename F>
__device__ __forceinline__ void cin_groups(const CinCtx& c, const uint32_t (&x)[10][2], float (&acc)[28], uint32_t (&z)[8],
                                           int q, bool more, uint32_t (&xn)[10][2], F finish) {
  if constexpr (G < GEND) {
    wg_fence();
    if constexpr (G == CG_LIN) {
      wgmma_rs_n32<CWL_DESC, 1>(acc, x[0][0], x[0][1], x[3][0], x[3][1]);
      wgmma_rs_n32<CWL_DESC + 1024 / 16, 1>(acc, x[6][0], x[6][1], x[9][0], x[9][1]);
    }
    z_mma<G>(acc, z);
    wg_commit();
    if constexpr (G == CG_LOAD) cin_load(c, q, more, xn);
    uint32_t zn[8];
    if constexpr (G + 1 < CG_N) z_fill<G + 1>(zn, x, c); else z_fill<0>(zn, xn, c);
    if constexpr (G == CG_FIN) finish();
    wg_wait<CG_WAIT>();
    if constexpr (G + 1 < GEND) cin_groups<G + 1, GEND>(c, x, acc, zn, q, more, xn, finish);
    else {
#pragma unroll
      for (int i = 0; i < 8; i++) z[i] = zn[i];
    }
    if constexpr (G + 1 < GEND) {
#pragma unroll
      for (int i = 0; i < 8; i++) z[i] = zn[i];
    }
  }
}
template <typename F>
__device__ __forceinline__ void cin_head(const CinCtx& c, uint32_t (&x)[10][2], float (&acc)[28], uint32_t (&z)[8], F finish) {
  cin_groups<0, CG_HEAD>(c, x, acc, z, 0, false, x, finish);
}
__device__ __forceinline__ void cin_tail(const CinCtx& c, const uint32_t (&x)[10][2], float (&acc)[28], uint32_t (&z)[8],
                                         int q, bool more, uint32_t (&xn)[10][2]) {
  cin_groups<CG_HEAD, CG_N>(c, x, acc, z, q, more, xn, []() {});
}

__device__ __forceinline__ int slot_of(int wg, int j) {
  return wg ? (j == 0 ? 9 * UNIT + XSLOT : j <= 8 ? 2 * UNIT + (j - 1) * XSLOT : 21 * UNIT + (j - 9) * XSLOT)
            : (j < 3 ? OFF_GIDX + j * XSLOT : 14 * UNIT + (j - 3) * XSLOT);
}

__device__ __forceinline__ void cin_begin(CinCtx& c, uint32_t sb, int wg, uint32_t first, uint32_t (&x)[10][2], float (&acc)[28], uint32_t (&z)[8]) {
  int t; asm volatile("mov.u32 %0, %%tid.x;" : "=r"(t));
  const int m = t & 16, f0 = t & 7, f1 = (f0 + 2) & 7, f2 = (f0 ^ 4) ^ (f0 >> 2);
  const uint32_t base = sb + m * 64, ch = (t & 96) + (t & 8) * 2;
  c.o03 = (base + f0 * 0x90) ^ ch;
  c.o14 = (base + f1 * 0x90) ^ ch;
  c.o25 = (base + f2 * 0x90) ^ ch;
  c.o69 = (base + 2048 + (m ? f0 & 1 : f0) * 0x90) ^ ch;
  c.o78 = m ? c.o25 + 1024 : c.o14 + 2048;
  mbar_wait(sb + OFF_BAR + 8 * BAR_GDONE, 0);
  mbar_wait(sb + OFF_BAR + 8 * (BAR_C0 + wg), 0);
  cin_ldsm(c, first, x);
  mbar_wait(sb + OFF_BAR + 8 * BAR_CW, 0);
  z_fill<0>(z, x, c);
  cin_head(c, x, acc, z, []() {});
}
__device__ __forceinline__ void cin_setup(CinCtx& c, uint32_t sb, int wg, int p, bool gemm, int nj, uint32_t zero) {
  c.bar = sb + (gemm ? OFF_BAR + 8 * (BAR_CFULL + wg * 8) : XOFF_BAR + wg * 16 * NPAIR);
  c.lead = (p & 31) == 0 && !gemm; c.ring = !gemm;
  c.so = !gemm ? XOFF_SLOT + 8 * wg * XSLOT : wg ? 2 * UNIT : OFF_GIDX + XSLOT;
  c.jump = c.so + (gemm && !wg ? 0 : 6 * XSLOT);
  c.dslot = !gemm ? -6 * XSLOT : wg ? 19 * UNIT - 6 * XSLOT : 14 * UNIT - OFF_GIDX - XSLOT;
  c.co = gemm ? c.so : (wg ? XOFF_CIN1 : XOFF_CIN0) - NF * 128;
  c.co2 = gemm ? XSLOT : CROW;
  c.so2 = c.so + XSLOT + zero;
  c.last = gemm ? slot_of(wg, (nj - 1) | 1) : c.co + ((nj - 1) & ~1) * CROW;
  c.cin = sb + NF * 128 + p * 4;
  const int q = p & 3;
  c.selA = q == 1 ? 0x7610 : 0x5410;
  c.selB = q == 0 ? 0x5432 : 0x7632;
  c.ones = q == 3;
}
template <typename F2, typename F3>
__device__ __forceinline__ void cin_run(CinCtx& c, int nj, uint32_t (&xA)[10][2], float (&accA)[28], uint32_t (&z)[8], F2 before_end, F3 st5) {
  float accB[28];
  uint32_t xB[10][2];
  const uint32_t lastA = nj & 1 ? c.last : 0;
#pragma unroll 1
  for (int j = 0;; j += 2) {
    cin_tail(c, xA, accA, z, 0, c.co != lastA, xB);
    if (c.co == lastA) { before_end(); wg_wait<0>(); cin_finish(c, accA, c.co); break; }
    cin_head(c, xB, accB, z, [&]() { st5(j); cin_finish(c, accA, c.co); });
    cin_tail(c, xB, accB, z, 1, true, xA);
    if (c.co == c.last) { before_end(); wg_wait<0>(); cin_finish(c, accB, c.co + c.co2); break; }
    cin_head(c, xA, accA, z, [&]() { st5(j + 1); cin_finish(c, accB, c.co + c.co2); });
    cin_advance(c);
  }
}

constexpr float ALPHA = 0.3292034911525734f, KAPPA = 2.423681954311584f;
__device__ __forceinline__ float gelu_acc(float v, float ab, float w, float s) {
  const float a = fmaf(v, ALPHA, ab);
  const float u = a * fmaf(a, a, KAPPA);
  float th; asm("tanh.approx.f32 %0, %1;" : "=f"(th) : "f"(u));
  return fmaf(fmaf(a, th, a), w, s);
}

constexpr int QD = 2;
template <int NG>
struct Gelu {
  float4 q[QD + 1];
  uint32_t ep;
  __device__ __forceinline__ void start(uint32_t a) {
    ep = a;
#pragma unroll
    for (int i = 0; i < QD; i++) q[i] = lds128f(ep + i * 64);
  }
  template <int I0, int I1>
  __device__ __forceinline__ void part(float (&d)[4 * NG], float& r0, float& r1) {
#pragma unroll
    for (int i = I0; i < I1; i++) {
      if (i + QD < NG) q[(i + QD) % (QD + 1)] = lds128f(ep + (i + QD) * 64);
      const float4 v = q[i % (QD + 1)];
#pragma unroll
      for (int e = 0; e < 4; e++) asm volatile("" : "+f"(d[4 * i + e]));
      r0 = gelu_acc(d[4 * i + 0], v.x, v.z, r0);
      r0 = gelu_acc(d[4 * i + 1], v.y, v.w, r0);
      r1 = gelu_acc(d[4 * i + 2], v.x, v.z, r1);
      r1 = gelu_acc(d[4 * i + 3], v.y, v.w, r1);
    }
    asm volatile("" : "+f"(r0), "+f"(r1));
  }
};
__device__ __forceinline__ float quad_sum(float r0, float r1, float r2, float r3, int lane) {
  const bool b0 = lane & 1, b1 = lane & 2;
  const float a = (b0 ? r1 : r0) + __shfl_xor_sync(0xffffffffu, b0 ? r0 : r1, 1);
  const float b = (b0 ? r3 : r2) + __shfl_xor_sync(0xffffffffu, b0 ? r2 : r3, 1);
  return (b1 ? b : a) + __shfl_xor_sync(0xffffffffu, b1 ? a : b, 2);
}
__device__ __forceinline__ void sts128f(uint32_t addr, float a, float b, float c, float d) {
  asm volatile("st.shared.v4.f32 [%0], {%1, %2, %3, %4};" ::"r"(addr), "f"(a), "f"(b), "f"(c), "f"(d) : "memory");
}
__device__ __forceinline__ void pin(float a, float b, uint32_t addr, uint32_t zero) {
  asm volatile("{\n.reg .pred p;\nsetp.ne.u32 p, %3, 0;\n@p st.shared.v2.f32 [%0], {%1, %2};\n}" ::"r"(addr), "f"(a), "f"(b), "r"(zero) : "memory");
}
__device__ __forceinline__ void hand_on(float (&d)[96], const float (&s)[96]) {
#pragma unroll
  for (int i = 0; i < 96; i++) asm volatile("mov.b32 %0, %1;" : "=f"(d[i]) : "f"(s[i]));
}
__device__ __forceinline__ uint64_t desc_x(int u) { return mkdesc(SMEM_BASE, 16, 1024, 1) + u * (UNIT / 16); }
__device__ __forceinline__ uint64_t desc_w(int u, int stride = 1) { return mkdesc(SMEM_BASE, stride * UNIT, 1024, 1) + u * (UNIT / 16); }
__device__ __forceinline__ void tile_step(float (&d)[96], uint64_t dA, uint64_t dB) {
  wg_fence();
#pragma unroll
  for (int k = 0; k < 4; k++) wgmma_ss_n192(d, dA + 2 * k, dB + 128 * k, 1);
  wg_commit();
}
template <int K0 = 0, int K1 = 4>
__device__ __forceinline__ void wide_step(float (&d)[96], float (&e)[32], uint64_t dA, uint64_t dB) {
  wg_fence();
#pragma unroll
  for (int k = K0; k < K1; k++) wgmma_ss_n256(d, e, dA + 2 * k, dB + 128 * k, 1);
  wg_commit();
}
__device__ __forceinline__ int cin_row(int c, int j) {
  if (c >= NGEMM) {
    const int e = (c - NGEMM) * NC_EXTRA + j;
    c = e < 256 ? e >> 1 : NBIG + e - 256;
    j = e < 256 ? 30 + (e & 1) : 29;
  }
  return (c >> 3) * 256 + (c & 2) * 64 + (c & 1) * 64 + (c & 4) * 8 + j;
}
__device__ __forceinline__ int cin_count(int c) {
  return c < NGEMM ? NC_GEMM + (c < NBIG) : NC_EXTRA;
}

__device__ __forceinline__ int fold_i0(int e) { return e < 2 ? 7 * e : 2 + 6 * e; }
__device__ __forceinline__ uint32_t ldg16(const void* p) { uint16_t v; asm volatile("ld.global.nc.u16 %0, [%1];" : "=h"(v) : "l"(p)); return v; }
__device__ __forceinline__ uint4 ldg128(const void* p) {
  uint4 v; asm volatile("ld.global.nc.v4.u32 {%0,%1,%2,%3}, [%4];" : "=r"(v.x), "=r"(v.y), "=r"(v.z), "=r"(v.w) : "l"(p)); return v;
}
__device__ __forceinline__ void sts64f(uint32_t addr, float a, float b) { asm volatile("st.shared.v2.f32 [%0], {%1, %2};" ::"r"(addr), "f"(a), "f"(b) : "memory"); }
__device__ __forceinline__ float to_tf32(float v) { uint32_t r; asm("cvt.rna.tf32.f32 %0, %1;" : "=r"(r) : "f"(v)); return __uint_as_float(r); }
__device__ __forceinline__ uint4 fold_chunk(uint32_t base, const uint4 t0, const uint4 t1) {
  const uint32_t t[8] = {t0.x, t0.y, t0.z, t0.w, t1.x, t1.y, t1.z, t1.w};
  uint32_t v[4];
#pragma unroll
  for (int c = 0; c < 4; c++) {
    const float w0 = __int_as_float(lds32(base + (t[2 * c] & 0xffff))) + __int_as_float(lds32(base + (t[2 * c] >> 16)));
    const float w1 = __int_as_float(lds32(base + (t[2 * c + 1] & 0xffff))) + __int_as_float(lds32(base + (t[2 * c + 1] >> 16)));
    __nv_bfloat162 pk = __floats2bfloat162_rn(w0, w1);
    v[c] = *reinterpret_cast<uint32_t*>(&pk);
  }
  return make_uint4(v[0], v[1], v[2], v[3]);
}
__device__ __forceinline__ int cw_chunk(int u, int n) {
  return ((u < 44 ? (u >> 1) * 1792 : CW_MAIN + ((u - 44) >> 1) * 1024) + (n >> 3) * 256 + (u & 1) * 128 + (n & 7) * 16) >> 4;
}
__device__ __forceinline__ void fold_weights(uint8_t* smem, uint32_t sb, int e, const __nv_bfloat16* __restrict__ wco, const GPtr gp) {
  const int tid = threadIdx.x, lane = tid & 31, warp = tid >> 5;
  const uint32_t bars = sb + OFF_BAR;
  const int i0 = fold_i0(e), i = i0 + warp;
  const bool own = i < fold_i0(e + 1);
  const uint32_t wb16 = ldg16(wco + (lane < NF ? 26 + lane : 0)), wc16 = ldg16(wco + (lane < NF ? 52 + lane : 0));
  const uint32_t w116 = ldg16(wco + (own ? i : 0));
  const uint4* tab = gp.tab;
  const uint4 ta0 = ldg128(tab + 2 * lane), ta1 = ldg128(tab + 2 * lane + 1);
  const uint4 tb0 = ldg128(tab + 64 + 2 * (lane & 15)), tb1 = ldg128(tab + 65 + 2 * (lane & 15));
  asm volatile("barrier.cluster.arrive.relaxed.aligned;\nbarrier.cluster.wait.acquire.aligned;" ::: "memory");
  if (warp >= 6) {
    for (int t = tid - 192; t < 6 * 20; t += 64) sts64f(sb + XOFF_M + 26 * 160 + t * 8, 0.f, 0.f);
    if (warp == 6 && lane < NF) {
      sts64f(sb + XOFF_M + lane * 160 + 104, bf_lo(wb16), 0.f);
      sts64f(sb + XOFF_M + lane * 160 + 112, 0.f, 0.f);
      sts64f(sb + XOFF_M + lane * 160 + 120, 0.f, 0.f);
    }
    if (warp == 7) {
      gp.s->cw[cw_chunk(lane, 28 + e)] = make_uint4(0, 0, 0, 0);
      if (lane < 16) gp.s->cw[cw_chunk(32 + lane, 28 + e)] = make_uint4(0, 0, 0, 0);
    }
  } else {
    mbar_wait(bars + 8 * BAR_GIDX, 0);
    float m0 = 0.f, m1 = 0.f, m2 = 0.f, m3 = 0.f;
    const uint32_t a = sb + XOFF_W3 + (tid < 169 ? tid : 0) * 8;
#pragma unroll 2
    for (int g = 0; g < NF; g++) {
      const int2 v = lds64(a + g * 1352);
      const float w = __shfl_sync(0xffffffffu, bf_lo(wc16), g);
      m0 = fmaf(w, bf_lo(v.x), m0); m1 = fmaf(w, bf_hi(v.x), m1);
      m2 = fmaf(w, bf_lo(v.y), m2); m3 = fmaf(w, bf_hi(v.y), m3);
    }
    if (tid < 169) {
      const int o = tid * 2, o2 = o + 1;
      sts64f(sb + XOFF_M + (o / 13) * 160 + (o % 13) * 8, to_tf32(m0), to_tf32(m1));
      sts64f(sb + XOFF_M + (o2 / 13) * 160 + (o2 % 13) * 8, to_tf32(m2), to_tf32(m3));
    }
  }
  const uint32_t sT = sb + XOFF_S + warp * 2 * 3136, sA = sT + 3136;
  const int g = lane >> 2, c = lane & 3;
  uint32_t af[2][8];
  mbar_wait(bars + 8 * BAR_FULL, 0);
  if (own) {
#pragma unroll
    for (int k = 0; k < 8; k++) {
      const int h = 4 * k + c;
      const uint32_t a = sb + XOFF_W2 + ((h < NF ? h : 0) * 676 + i * 26 + 2 * g) * 2;
      af[0][k] = lds32(a);
      af[1][k] = lds32(a + (g < 5 ? 32 : 0));
    }
#pragma unroll 1
    for (int o = lane; o < 338; o += 32) {
      const uint32_t v = lds32(sb + XOFF_W1 + (i - (i0 & ~1)) * 1352 + o * 4);
      sts64f(sA + (o / 13) * 112 + (o % 13) * 8, bf_lo(v), bf_hi(v));
    }
    if (lane < 28) sts64f(sA + lane * 112 + 104, 0.f, 0.f);
    if (lane < 2) sts64f(sT + (26 + lane) * 112 + 104, lane == 0 ? bf_lo(w116) : 0.f, 0.f);
  }
  bar_sync<4, 256>();
  if (own) {
#pragma unroll 1
    for (int n = 0; n < 4; n++) {
      float d[2][4] = {};
#pragma unroll
      for (int ks = 0; ks < 4; ks++) {
        const uint32_t b0 = lds32(sb + XOFF_M + (8 * ks + c) * 160 + (8 * n + g) * 4);
        const uint32_t b1 = lds32(sb + XOFF_M + (8 * ks + c + 4) * 160 + (8 * n + g) * 4);
#pragma unroll
        for (int m = 0; m < 2; m++)
          asm volatile("mma.sync.aligned.m16n8k8.row.col.f32.tf32.tf32.f32 {%0,%1,%2,%3}, {%4,%5,%6,%7}, {%8,%9}, {%0,%1,%2,%3};"
                       : "+f"(d[m][0]), "+f"(d[m][1]), "+f"(d[m][2]), "+f"(d[m][3])
                       : "r"(af[m][2 * ks] << 16), "r"(af[m][2 * ks] & 0xffff0000u), "r"(af[m][2 * ks + 1] << 16),
                         "r"(af[m][2 * ks + 1] & 0xffff0000u), "r"(b0), "r"(b1));
      }
      if (n < 3 || c < 2) {
        const uint32_t a = sT + 2 * g * 112 + (8 * n + 2 * c) * 4;
        sts64f(a, d[0][0], d[0][1]);
        sts64f(a + 112, d[0][2], d[0][3]);
        if (g < 5) {
          sts64f(a + 16 * 112, d[1][0], d[1][1]);
          sts64f(a + 17 * 112, d[1][2], d[1][3]);
        }
      }
    }
    __syncwarp();
    const int nt = i < 24 ? i : 2 * i - 24, na = i < 24 ? 32 + i : 2 * i - 23;
#pragma unroll 1
    for (int k = 0; k < 3; k++) {
      const bool isa = k == 1 || (k == 2 && lane >= 16);
      const uint4 v = fold_chunk(isa ? sA : sT, k < 2 ? ta0 : tb0, k < 2 ? ta1 : tb1);
      if (k < 2 || lane < 28 || na < 32) gp.s->cw[cw_chunk(k < 2 ? lane : 32 + (lane & 15), isa ? na : nt)] = v;
    }
  }
  __syncwarp();
  if (lane == 0) flag_add(&gp.s->foldflag);
  bar_sync<4, 256>();
  mbar_wait(bars + 8 * BAR_GDONE, 0);
  if (tid >= 128 && tid < 132) mbar_arrive(ev_bar(bars, EV_END));
}

__global__ void __cluster_dims__(2, 1, 1) __launch_bounds__(384, 1)
xdeepfm_kernel(const int* __restrict__ idx, const __nv_bfloat16* __restrict__ table, const __nv_bfloat16* __restrict__ w1,
               const __nv_bfloat16* __restrict__ b1, const __nv_bfloat16* __restrict__ w2,
               const __nv_bfloat16* __restrict__ ws, const __nv_bfloat16* __restrict__ wco,
               const __nv_bfloat16* __restrict__ bout, __nv_bfloat16* __restrict__ out, const GPtr gp,
               const __grid_constant__ CUtensorMap tmW, const __grid_constant__ CUtensorMap tmT,
               const __grid_constant__ CUtensorMap tmS, const __grid_constant__ CUtensorMap tmC) {
  int myidx, idx1, idx2 = 0, idx3 = 0;
  {
    const int t = threadIdx.x, b = blockIdx.x, half = (b >> 1) ^ (t >= 256 ? t >> 4 : 0);
    const int* ip = idx + (((b >> 3) & 15) * 256 + (half & 1) * 128 + (t < 256 ? t >> 1 : (b & 1) * 64 + ((t >> 1) & 48) + (t & 15))) * NF;
    asm volatile("{\n.reg .pred p;\nsetp.ge.u32 p, %5, 256;\nld.global.nc.v2.s32 {%0, %1}, [%4];\n@p ld.global.nc.v2.s32 {%2, %3}, [%4 + 8];\n}"
                 : "=r"(myidx), "=r"(idx1), "+r"(idx2), "+r"(idx3) : "l"(ip), "r"(t));
  }
  extern __shared__ __align__(1024) uint8_t smem[];
  const uint32_t sb = (uint32_t)__cvta_generic_to_shared(smem);
  const uint32_t bars = sb + OFF_BAR;
  const int tid = threadIdx.x, lane = tid & 31;
  const int warp = __shfl_sync(0xffffffffu, tid >> 5, 0);
  const int cta = blockIdx.x;
  const bool gemm = cta < NGEMM;
  const int nt = cta & 7, rank = cta & 1;

  if (warp == 8 && elect1()) {
    mbar_init(bars + 8 * BAR_GIDX, 1);
    mbar_init(bars + 8 * BAR_FULL, 1);
    mbar_init(bars + 8 * BAR_W0, 1);
    asm volatile("fence.mbarrier_init.release.cluster;" ::: "memory");
    if (gemm) {
      mbar_expect_tx(bars + 8 * BAR_W0, 4 * UNIT);
#pragma unroll
      for (int i = 0; i < 4; i++)
        tma_load(sb + (U_W + i) * UNIT, &tmW, i < 3 ? nt * 192 + i * 64 : 1536 + (nt >> 2) * 64, 0, bars + 8 * BAR_W0);
    } else {
      mbar_expect_tx(bars + 8 * BAR_GIDX, 35152);
      bulk_load(sb + XOFF_W3, ws + 2 * 17576, 35152, bars + 8 * BAR_GIDX);
    }
  }
  if (threadIdx.x < 256) {}
  else if (threadIdx.x >= 384 - 16) {
    const int l = threadIdx.x & 7;
    if (l < 7) asm volatile("prefetch.global.L2 [%0];" ::"l"(w1 + (((cta >> 3 & 15) * 2 + (cta & 1)) * 2 + ((threadIdx.x >> 3) & 1)) * DIN + (l < 6 ? (cta & 6) * 192 + l * 64 : 1536 + (cta & 4) * 16)));
  }
  else if (threadIdx.x >= 352 && threadIdx.x < 359) {
    const int l = blockIdx.x * 7 + threadIdx.x - 352;
    if (l < 824) asm volatile("prefetch.global.L2 [%0];" ::"l"(ws + (823 - l) * 64));
  }

  if (warp >= 8) {
    const int pw = warp - 8;
    const bool lead = elect1();
    if (lead) {
      if (pw) mbar_init(bars + 8 * (pw < 3 ? BAR_FULL + pw : BAR_X0), 1);
      else mbar_init(bars + 8 * BAR_GDONE, 4);
      asm volatile("fence.mbarrier_init.release.cluster;" ::: "memory");
    }
    __syncwarp();
    asm volatile("barrier.cluster.arrive.relaxed.aligned;" ::: "memory");
    if (lead) {
      if (gemm) w_prefetch(w1, 1, cta, pw);
      if (pw == 0) {
        if (gemm) {
          mbar_expect_tx(bars + 8 * BAR_FULL, 2 * UNIT);
          asm volatile("prefetch.tensormap [%0];" ::"l"(&tmT) : "memory");
          asm volatile("prefetch.tensormap [%0];" ::"l"(&tmS) : "memory");
        } else {
          const int i0 = fold_i0(cta - NGEMM) & ~1, ni = NF - i0 < 8 ? NF - i0 : 8;
          mbar_expect_tx(bars + 8 * BAR_FULL, 35152 + ni * 1352);
          bulk_load(sb + XOFF_W1, ws + i0 * 676, ni * 1352, bars + 8 * BAR_FULL);
          bulk_load(sb + XOFF_W2, ws + 17576, 35152, bars + 8 * BAR_FULL);
        }
      }
    }
    __syncwarp();
    asm volatile("setmaxnreg.dec.sync.aligned.u32 24;");
    if (elect1()) {
      mbar_init(bars + 8 * (BAR_EV + pw), 4);
      mbar_init(bars + 8 * (BAR_EV + 4 + pw), 4);
      mbar_init(bars + 8 * (BAR_FULL + 4 + pw), 1);
      if (pw < 3) mbar_init(bars + 8 * (pw == 2 ? BAR_CW : BAR_DNN + pw), pw == 0 && !gemm ? 4 : 1 + (pw & 1));
      if (pw < 2) mbar_init(bars + 8 * (pw ? BAR_PARK : BAR_FULL + 3), 1 + 7 * pw);
#pragma unroll
      for (int i = 0; i < 4; i++) mbar_init(bars + 8 * (BAR_CFULL + pw * 4 + i), 1);
      if (pw < 2) mbar_init(bars + 8 * (BAR_C0 + pw), 1);
      asm volatile("fence.mbarrier_init.release.cluster;" ::: "memory");
    }
    __syncwarp();
    bar_sync<6, 128>();
    asm volatile("barrier.cluster.wait.acquire.aligned;" ::: "memory");
    if (gemm) {
      {
        const uint32_t a = sb + OFF_GIDX + ((lane >> 4) * 64 + pw * 16 + (lane & 15)) * NF * 4;
        asm volatile("st.shared.v2.b32 [%0], {%1, %2};\nst.shared.v2.b32 [%0 + 8], {%3, %4};"
                     ::"r"(a), "r"(myidx), "r"(idx1), "r"(idx2), "r"(idx3) : "memory");
        __syncwarp();
      }
      if (elect1()) {
#pragma unroll
        for (int j = 0; j < 16; j += 8) {
          int r[8];
#pragma unroll
          for (int i = 0; i < 8; i++) r[i] = lds32(sb + OFF_GIDX + ((64 + pw * 16 + j + i) * NF) * 4);
#pragma unroll
          for (int i = 0; i < 8; i++) tma_row_mc(sb + U_XB * UNIT + (rank * 64 + pw * 16 + j + i) * 128, &tmT, r[i], bars + 8 * BAR_FULL);
        }
        int s = 1;
#pragma unroll 1
        for (int fi = 1; fi < NF; fi++) {
          const int f = fresh(fi), pw = fresh(warp) - 8, ct = fresh(cta), nt = ct & 7;
          const int t = f - FS, st = t < 0 ? s : (t & 3) ^ ((t >> 1) & 1), e = f - 3 - (t > 1);
          const uint32_t fb = bars + 8 * (BAR_FULL + (f & 7)), ia = sb + OFF_GIDX + (pw * 16 * NF + f) * 4;
          const uint32_t d = sb + (st == 3 ? U_SP : 2 * st) * UNIT + ((ct & 1) * 64 + pw * 16) * 128;
          if (f == 4) mbar_wait(bars + 8 * BAR_GIDX, 0);
          int r[2][RB];
#pragma unroll
          for (int i = 0; i < RB; i++) r[0][i] = lds32(ia + i * NF * 4);
          if (e >= 0) mbar_wait(ev_bar(bars, e), ev_par(e));
          if (pw == 0) mbar_expect_tx(fb, t < 0 ? 8 * UNIT : 6 * UNIT);
#pragma unroll
          for (int j = 0; j < 16 / RB; j++) {
#pragma unroll
            for (int i = 0; i < RB; i++) r[(j + 1) & 1][i] = lds32(ia + (RB * j + RB + i + (RB * j + RB >= 16) * 48) * NF * 4);
#pragma unroll
            for (int i = 0; i < RB; i++) tma_row_mc(d + (RB * j + i) * 128, &tmT, r[j & 1][i], fb);
          }
          if (t < 0) {
#pragma unroll
            for (int j = 0; j < 16 / RB; j++) {
              if (j + 1 < 16 / RB) {
#pragma unroll
                for (int i = 0; i < RB; i++) r[(j + 1) & 1][i] = lds32(ia + (64 + RB * j + RB + i) * NF * 4);
              }
#pragma unroll
              for (int i = 0; i < RB; i++) tma_row_mc(d + U_XB * UNIT + (RB * j + i) * 128, &tmT, r[j & 1][i], fb);
            }
          }
          tma_load(sb + (U_W + 4 * st + pw) * UNIT, &tmW, pw < 3 ? nt * 192 + pw * 64 : 1536 + (nt >> 2) * 64, f * 64, fb);
          if (f == GI && pw < 2) {
            if (pw == 0) mbar_expect_tx(bars + 8 * BAR_GIDX, 128 * NF * 4);
            bulk_load(sb + OFF_GIDX + pw * 64 * NF * 4, idx + ((ct >> 3) * 256 + (((ct >> 1) ^ pw) & 1) * 128 + (ct & 1) * 64) * NF, 64 * NF * 4, bars + 8 * BAR_GIDX);
          }
          if (f == GI && pw == 2) asm volatile("prefetch.tensormap [%0];" ::"l"(&tmC) : "memory");
          if (f + WD < NF) w_prefetch(w1, f + WD, ct, pw);
          if (++s == 3) s = 0;
        }
        mbar_wait(bars + 8 * BAR_T, 0);
#pragma unroll 1
        for (int ti = 0; ti < 8; ti++) {
          const int t = fresh(ti), pw = fresh(warp) - 8, e = t < 4 ? 22 - !t : 19 + t;
          const uint32_t ia = sb + OFF_TIDX + t * 256 + pw * 64, fb = bars + 8 * (BAR_FULL + ((NF + t) & 7));
          const uint32_t d = sb + b_x(t) * UNIT + ((fresh(cta) & 1) * 64 + pw * 16) * 128;
          int4 r[2];
          r[0] = lds128(ia);
          r[1] = lds128(ia + 16);
          mbar_wait(ev_bar(bars, e), ev_par(e));
          if (pw == 0) mbar_expect_tx(fb, t < 3 ? 2 * UNIT : 5 * UNIT);
#pragma unroll
          for (int j = 0; j < 4; j++) {
            tma_row_mc(d + (4 * j + 0) * 128, &tmT, r[j & 1].x, fb);
            tma_row_mc(d + (4 * j + 1) * 128, &tmT, r[j & 1].y, fb);
            tma_row_mc(d + (4 * j + 2) * 128, &tmT, r[j & 1].z, fb);
            tma_row_mc(d + (4 * j + 3) * 128, &tmT, r[j & 1].w, fb);
            if (j < 2) r[j & 1] = lds128(ia + 32 + 16 * j);
          }
        }
        mbar_arrive(bars + 8 * BAR_GDONE);
      }
      __syncwarp();
    }
    asm volatile("setmaxnreg.inc.sync.aligned.u32 %0;" ::"n"(PREG));
    {
    int cta; asm volatile("mov.u32 %0, %%ctaid.x;" : "=r"(cta));
    cta = __shfl_sync(0xffffffffu, cta, 0);
    const bool gemm = cta < NGEMM;
    const int bt = cta >> 3, nt = cta & 7;
    const int ncin = cin_count(cta);
    unsigned epoch = lds32(bars + 8 * BAR_EPOCH);
    if (!gemm) {
      epoch = gp.s->epoch[cta] + 1;
#pragma unroll 1
      for (int i = pw * 32 + lane; i < NC_EXTRA * 13; i += 128)
        asm volatile("cp.async.ca.shared.global [%0], [%1], 8;" ::"r"(sb + XOFF_CIDX + i * 8), "l"(idx + cin_row(cta, i / 13) * NF + i % 13 * 2) : "memory");
      if (elect1()) {
#pragma unroll 1
        for (int i = 0; i < NPAIR; i++) mbar_init(sb + XOFF_BAR + (pw * NPAIR + i) * 8, pw & 1 ? 4 : 1);
        asm volatile("fence.mbarrier_init.release.cluster;" ::: "memory");
      }
      asm volatile("cp.async.wait_all;" ::: "memory");
      bar_sync<6, 128>();
      if (elect1()) mbar_arrive(bars + 8 * BAR_GDONE);
      __syncwarp();
    }
    if (pw == 3) {
      if (elect1()) {
        if (!gemm) flag_wait(&gp.s->foldflag, epoch * NEXTRA * 8, 0);
        asm volatile("fence.proxy.async.global;" ::: "memory");
        if (gemm) mbar_wait(ev_bar(bars, EV_CW), ev_par(EV_CW));
        mbar_expect_tx(bars + 8 * BAR_CW, CW_BYTES);
        bulk_load(sb + OFF_CW, gp.s->cw, CW_CUT * 1792, bars + 8 * BAR_CW);
        bulk_load(sb + OFF_CW2, gp.s->cw + CW_CUT * 1792 / 16, (22 - CW_CUT) * 1792, bars + 8 * BAR_CW);
        bulk_load(sb + OFF_CWL, gp.s->cw + CW_MAIN / 16, CW_LIN, bars + 8 * BAR_CW);
      }
      __syncwarp();
    }
    if (!gemm) {
      if (elect1()) {
        const int wg = pw & 1;
#pragma unroll 1
        for (int t = pw < 2 ? -1 : 1; t < NPAIR; t += t < 0 ? 1 : 2) {
          const int j = t < 0 ? 0 : 2 * t + 1, n = t < 0 || t == NPAIR - 1 ? 1 : 2;
          const uint32_t cb = t < 0 ? bars + 8 * (BAR_C0 + wg) : sb + XOFF_BAR + (wg * 2 * NPAIR + t) * 8;
          if (t == 0 || t == 1) mbar_wait(ev_bar(bars, EV_END), ev_par(EV_END));
          if (t >= 4) mbar_wait(cb + 8 * (NPAIR - 4), 0);
          mbar_expect_tx(cb, n * NF * 128);
#pragma unroll 1
          for (int i = 0; i < n; i++) {
            const uint32_t d = sb + (t < 0 ? OFF_GIDX + wg * XSLOT : XOFF_SLOT + (wg * 8 + (t & 3) * 2 + i) * XSLOT);
            const uint32_t ia = sb + XOFF_CIDX + (wg * (NC_EXTRA / 2) + j + i) * NF * 4;
#pragma unroll
            for (int k = 0; k < NF; k += 2) {
              const int2 r = lds64(ia + k * 4);
              tma_row(d + k * 128, &tmT, r.x, cb);
              tma_row(d + (k + 1) * 128, &tmT, r.y, cb);
            }
          }
        }
      }
      __syncwarp();
    } else {
      constexpr int n0 = NC_WG0;
      const uint32_t ep = sb + OFF_EPI + (lane & 3) * 16, pk = sb + (pw * 32 + lane) * 16;
      float r2 = 0.f, r3 = 0.f;
#pragma unroll 1
      for (int k = 0; k < 5; k++) {
        if (elect1()) {
          const int n = pw + 4 * k, wg = n > 1 && ((n & 1) || n == 2), j = n == 1 ? 1 : n < 3 ? 0 : n - 1 - wg;
          const int m = min((wg ? ncin - n0 : n0) - j, j ? 2 : 1);
          const uint32_t cb = bars + 8 * (j ? BAR_CFULL + wg * 8 + (j >> 1) : BAR_C0 + wg);
          if (k == 0) {
            mbar_wait(bars + 8 * BAR_GDONE, 0);
            mbar_wait(bars + 8 * BAR_X0, 0);
            asm volatile("fence.proxy.async.global;" ::: "memory");
          }
          if (n >= 2 && n < 12) {
            const int e = n == 2 ? EV_CW : n < 7 ? EV_SLOT : EV_END;
            mbar_wait(ev_bar(bars, e), ev_par(e));
          }
          if (m > 0) mbar_expect_tx(cb, m * NF * 128);
#pragma unroll 1
          for (int i = 0; i < m; i++) {
            const int r = wg * n0 + j + i;
            const uint32_t d = sb + slot_of(wg, j) + i * XSLOT;
            const int4 u = lds128(sb + OFF_CIDX + r * 32), v = lds128(sb + OFF_CIDX + r * 32 + 16);
            tma_row(d, &tmC, (cta * 32 + r) * FS, cb);
            tma_row(d + (FS + 0) * 128, &tmT, u.x, cb);
            tma_row(d + (FS + 1) * 128, &tmT, u.y, cb);
            tma_row(d + (FS + 2) * 128, &tmT, u.z, cb);
            tma_row(d + (FS + 3) * 128, &tmT, u.w, cb);
            tma_row(d + (FS + 4) * 128, &tmT, v.x, cb);
            tma_row(d + (FS + 5) * 128, &tmT, v.y, cb);
            tma_row(d + (FS + 6) * 128, &tmT, v.z, cb);
            tma_row(d + (FS + 7) * 128, &tmT, v.w, cb);
          }
        }
        __syncwarp();
        if (k == 0 || k == 4) continue;
        if (k == 1) {
          mbar_wait(bars + 8 * BAR_PARK, 0);
        }
        uint32_t a = pk + (k == 3 ? OFF_PARK2 : OFF_PARK + (k - 1) * 8 * 2048), b = ep + (k - 1) * 8 * 64;
#pragma unroll 1
        for (const uint32_t e = b + 8 * 64; b != e; a += BGN * 2048, b += BGN * 64) {
          float4 v[BGN], q[BGN];
#pragma unroll
          for (int i = 0; i < BGN; i++) { v[i] = lds128f(a + i * 2048); q[i] = lds128f(b + i * 64); }
#pragma unroll
          for (int i = 0; i < BGN; i++) {
            r2 = gelu_acc(v[i].x, q[i].x, q[i].z, r2);
            r3 = gelu_acc(v[i].z, q[i].x, q[i].z, r3);
            r2 = gelu_acc(v[i].y, q[i].y, q[i].w, r2);
            r3 = gelu_acc(v[i].w, q[i].y, q[i].w, r3);
          }
        }
      }
      const float4 w = lds128f(pk + OFF_RS0);
      const int2 v = lds64(sb + OFF_RS1 + (pw * 32 + lane) * 8);
      uint2* dst = gp.s->part + nt * NB + bt * 256 + pw * 16 + (lane & 1) * 8 + (lane >> 2);
      put_tagged(dst + (cta & 2) * 64 + (((lane >> 1) ^ ~cta) & 1) * 64, quad_sum(w.x, w.y, w.z, w.w, lane), epoch);
      put_tagged(dst + (~cta & 2) * 64 + (lane & 2) * 32, quad_sum(__int_as_float(v.x), __int_as_float(v.y), r2, r3, lane), epoch);
    }
    if (pw == 3 || !gemm) {
      float s = (sb & 0xFFFFFF) == SMEM_BASE ? bf2f(bout[0]) : __int_as_float(0x7fc00000);
      const int r = gemm ? lane : pw * (NC_EXTRA / 4) + min(lane, NC_EXTRA / 4 - 1), row = cin_row(cta, r);
      const uint2* src = gp.s->part + row;
      uint2 v[8];
#pragma unroll 1
      for (int i = 0; i < 100000; i++) {
        unsigned miss = 0;
#pragma unroll
        for (int n = 0; n < 8; n++)
          asm volatile("ld.relaxed.gpu.global.v2.b32 {%0, %1}, [%2];" : "=r"(v[n].x), "=r"(v[n].y) : "l"(src + n * NB) : "memory");
#pragma unroll
        for (int n = 0; n < 8; n++) miss |= v[n].y ^ epoch;
        if (__all_sync(0xffffffffu, miss == 0)) break;
        __nanosleep(POLL);
      }
#pragma unroll
      for (int n = 0; n < 8; n++) s += __uint_as_float(v[n].x);
      sts64f(sb + OFF_DNN + r * 8, s, __int_as_float(row));
      __syncwarp();
      if (lane == 0) mbar_arrive(bars + 8 * BAR_DNN);
      if (pw == 3 && lane == 0) gp.s->epoch[fresh(cta)] = epoch;
    }
    }
  } else {
    const int wg = warp >> 2;
    const int p = tid & 127;
    if (gemm) {
      asm volatile("barrier.cluster.arrive.relaxed.aligned;" ::: "memory");
#pragma unroll
      for (int i = 0; i < 4; i++) {
        const int r = __shfl_sync(0xffffffffu, myidx, 8 * i + 2 * (lane >> 3));
        const int row = warp * 16 + 4 * i + (lane >> 3);
        cpasync16(sb + row * 128 + (((lane & 7) ^ (row & 7)) << 4), table + (size_t)r * 64 + (lane & 7) * 8);
      }
      asm volatile("barrier.cluster.wait.acquire.aligned;" ::: "memory");
    } else {
      fold_weights(smem, sb, cta - NGEMM, wco, gp);
    }
    asm volatile("setmaxnreg.inc.sync.aligned.u32 224;");
    float r0 = 0.f, r1 = 0.f, r2 = 0.f, r3 = 0.f;
    CinCtx c;
    float accA[28];
    uint32_t xA[10][2], z[8];
    const uint32_t ep = sb + OFF_EPI + (lane & 3) * 16;
    auto load_w = [&](int t) {
      const int w = warp & 3;
      if (w < 3 && elect1())
        tma_load(sb + (b_w(t) + b_ws(t) * w) * UNIT, &tmW, nt * 192 + w * 64, (NF - 1 - t) * 64, bars + 8 * (BAR_FULL + ((NF + t) & 7)));
    };
    auto keep_x = [&](int f, int u) {
      if (warp == 0 && elect1()) tma_store(&tmS, f * 64, cta * 32, sb + (u + rank) * UNIT + (nt >> 2) * 4096);
    };
    auto role = [&](int w) { int c; asm volatile("mov.u32 %0, %%ctaid.x;" : "=r"(c)); return c < NGEMM && wg == w; };
    if (role(0)) {
      asm volatile("setmaxnreg.inc.sync.aligned.u32 256;");
      float d0[96], dx[32], dw[96];
      Gelu<24> g0;
      mbar_wait(bars + 8 * BAR_W0, 0);
      asm volatile("cp.async.wait_all;" ::: "memory");
      asm volatile("fence.proxy.async.shared::cta;" ::: "memory");
      bar_sync<2, 256>();
      const uint64_t dA0 = desc_x(rank), dA1 = desc_x(rank ^ 1);
      wg_fence();
#pragma unroll
      for (int k = 0; k < 4; k++) {
        wgmma_ss_n256(dw, dx, dA0 + 2 * k, desc_w(U_W) + 128 * k, k != 0);
        wgmma_ss_n192(d0, dA1 + 2 * k, desc_w(U_W) + 128 * k, k != 0);
      }
      wg_commit();
      keep_x(0, 0);
#pragma unroll 1
      for (int f = 1; f < NF - 3; f++) {
        mbar_wait(bars + 8 * (BAR_FULL + (f & 7)), (f >> 3) & 1);
        const int st = (STAGES >> (2 * f)) & 3, xo = (st == 3 ? U_SP : 2 * st) * (UNIT / 16);
        const uint64_t dB = desc_w(U_W + 4 * st);
        wg_fence();
        wgmma_ss_n256(dw, dx, dA0 + xo, dB, 1);
        wgmma_ss_n192(d0, dA1 + xo, dB, 1);
        wg_commit();
        store_read<0>();
        wg_wait<1>();
        if (p < (f > FS ? 4 : 2)) mbar_arrive_cta(ev_bar(bars, f - 1), p & 1);
#pragma unroll
        for (int k = 1; k < 4; k++) {
          wgmma_ss_n256(dw, dx, dA0 + xo + 2 * k, dB + 128 * k, 1);
          wgmma_ss_n192(d0, dA1 + xo + 2 * k, dB + 128 * k, 1);
        }
        wg_commit();
        if (f < FS) keep_x(f, 2 * st);
      }
      {
        constexpr int x3 = 2 * (UNIT / 16), x4 = U_SP * (UNIT / 16), x5 = 4 * (UNIT / 16);
        const uint64_t dB3 = desc_w(U_W + 4), dB4 = desc_w(U_W + 12), dB5 = desc_w(U_W + 8);
        mbar_wait(bars + 8 * (BAR_FULL + 7), 0);
        tile_step(d0, dA1 + x3, dB3);
        wg_wait<1>();
        if (p < 4) mbar_arrive_cta(ev_bar(bars, NF - 4), p & 1);
        mbar_wait(bars + 8 * (BAR_FULL + 0), 1);
        tile_step(d0, dA1 + x4, dB4);
        mbar_wait(bars + 8 * (BAR_FULL + 1), 1);
        tile_step(d0, dA1 + x5, dB5);
        wide_step(dw, dx, dA0 + x3, dB3);
        g0.start(ep);
        wg_wait<1>();
        wide_step(dw, dx, dA0 + x4, dB4);
        g0.part<0, PE1>(d0, r0, r1);
        pin(r0, r1, ep, gp.zero);
        wg_wait<1>();
        if (p < 4) mbar_arrive_cta(ev_bar(bars, NF - 3), p & 1);
        wide_step<0, HK>(dw, dx, dA0 + x5, dB5);
        g0.part<PE1, PE2>(d0, r0, r1);
        pin(r0, r1, ep, gp.zero);
        wg_wait<1>();
        bar_arrive<4, 256>();
        if (p < 4) mbar_arrive_cta(ev_bar(bars, NF - 2), p & 1);
        wide_step<HK, 4>(dw, dx, dA0 + x5, dB5);
        g0.part<PE2, PE0>(d0, r0, r1);
        pin(r0, r1, ep, gp.zero);
        wg_wait<0>();
        load_w(3);
        if (p < 4) mbar_arrive_cta(ev_bar(bars, NF - 1), p & 1);
        asm volatile("cp.async.bulk.wait_group 0;" ::: "memory");
        if (warp == 0 && elect1()) mbar_arrive(bars + 8 * BAR_X0);
      }
      g0.part<PE0, 24>(d0, r0, r1);
      Gelu<8> gx;
      gx.start(ep + 24 * 64);
      gx.part<0, 8>(dx, r2, r3);
      float d1[96];
      hand_on(d1, dw);
      asm volatile("setmaxnreg.dec.sync.aligned.u32 224;");
      Gelu<24> g1;
      g1.start(ep);
      g1.part<0, 24>(d1, r2, r3);
    }
    if (role(1)) {
      float d0[96], dw[96];
      asm volatile("cp.async.wait_all;" ::: "memory");
      asm volatile("fence.proxy.async.shared::cta;" ::: "memory");
      bar_arrive<2, 256>();
      {
        const int col = p < 96 ? nt * 96 + p : 768 + (nt >> 2) * 32 + (p - 96);
        const uint32_t bb = __ldg(reinterpret_cast<const uint32_t*>(b1) + col), ww = __ldg(reinterpret_cast<const uint32_t*>(w2) + col);
        reinterpret_cast<float4*>(smem + OFF_EPI)[p] =
            make_float4(ALPHA * bf_lo(bb), ALPHA * bf_hi(bb), (0.5f / ALPHA) * bf_lo(ww), (0.5f / ALPHA) * bf_hi(ww));
      }
      mbar_wait(bars + 8 * BAR_W0, 0);
      mbar_wait(bars + 8 * BAR_FULL, 0);
      wg_fence();
#pragma unroll
      for (int k = 0; k < 4; k++) {
        wgmma_ss_n192(d0, desc_x(U_XB) + 2 * k, desc_w(U_W) + 128 * k, k != 0);
        wgmma_ss_n192(dw, desc_x(U_XB + 1) + 2 * k, desc_w(U_W) + 128 * k, k != 0);
      }
      wg_commit();
      int s = 1;
#pragma unroll 1
      for (int f = 1; f < FS; f++) {
        mbar_wait(bars + 8 * (BAR_FULL + (f & 7)), (f >> 3) & 1);
        const uint64_t dA = desc_x(U_XB + 2 * s), dB = desc_w(U_W + 4 * s);
        wg_fence();
        wgmma_ss_n192(d0, dA, dB, 1);
        wgmma_ss_n192(dw, dA + 512, dB, 1);
        wg_commit();
        wg_wait<1>();
        if (p < 2) mbar_arrive_cta(ev_bar(bars, f - 1), p);
#pragma unroll
        for (int k = 1; k < 4; k++) {
          wgmma_ss_n192(d0, dA + 2 * k, dB + 128 * k, 1);
          wgmma_ss_n192(dw, dA + 512 + 2 * k, dB + 128 * k, 1);
        }
        wg_commit();
        if (++s == 3) s = 0;
      }
      wg_wait<0>();
      if (p < 2) mbar_arrive_cta(ev_bar(bars, FS - 1), p);
      {
        const uint32_t a = sb + OFF_GIDX + 64 * NF * 4;
        int v[4];
#pragma unroll
        for (int i = 0; i < 4; i++) v[i] = lds32(a + (((p & 15) * 4 + i) * NF + (NF - 1 - (p >> 4))) * 4);
        const int2 w = lds64(sb + OFF_GIDX + (((nt >> 2) * 32 + (p >> 2)) * NF + FS + (p & 3) * 2) * 4);
        asm volatile("st.shared.v2.b32 [%0], {%1, %2};" ::"r"(sb + OFF_CIDX + p * 8), "r"(w.x), "r"(w.y) : "memory");
        bar_sync<3, 128>();
        asm volatile("st.shared.v4.b32 [%0], {%1, %2, %3, %4};" ::"r"(sb + OFF_TIDX + p * 16), "r"(v[0]), "r"(v[1]), "r"(v[2]), "r"(v[3]) : "memory");
        bar_sync<3, 128>();
        if (p < 2) {
          const unsigned epoch = gp.s->epoch[cta] + 1;
          flag_wait(&gp.s->foldflag, epoch * NEXTRA * 8, 0);
          sts32f(bars + 8 * BAR_EPOCH, __uint_as_float(epoch));
          mbar_arrive(bars + 8 * BAR_T);
        }
        __syncwarp();
      }
      mbar_wait(ev_bar(bars, FS), ev_par(FS));
      mbar_wait(bars + 8 * (BAR_FULL + 2), 1);
      bar_sync<4, 256>();
#pragma unroll
      for (int t = 0; t < 4; t++) {
        if (t) mbar_wait(bars + 8 * (BAR_FULL + 2 + t), 1);
        const uint64_t dA = desc_x(b_x(t)), dB = desc_w(b_w(t), b_ws(t));
        wg_fence();
#pragma unroll
        for (int k = 0; k < 4; k++) {
          wgmma_ss_n192(d0, dA + 2 * k, dB + 128 * k, 1);
          wgmma_ss_n192(dw, dA + 512 + 2 * k, dB + 128 * k, 1);
          if (k == 1 && t) {
            wg_commit();
            wg_wait<1>();
            wg_fence();
          }
        }
        wg_commit();
        if (t) {
          if (t == 1) mbar_wait(ev_bar(bars, NF - 1), ev_par(NF - 1));
          load_w(3 + t);
          if (t == 1 && p < 4) mbar_arrive_cta(ev_bar(bars, 26), p & 1);
        }
      }
      mbar_wait(bars + 8 * (BAR_FULL + 6), 1);
      tile_step(d0, desc_x(b_x(4)), desc_w(b_w(4)));
      wg_wait<1>();
      load_w(7);
      if (p < 4) mbar_arrive(ev_bar(bars, EV_CW));
      mbar_wait(bars + 8 * (BAR_FULL + 7), 1);
      tile_step(d0, desc_x(b_x(5)), desc_w(b_w(5)));
      mbar_wait(bars + 8 * (BAR_FULL + 0), 0);
      tile_step(d0, desc_x(b_x(6)), desc_w(b_w(6)));
      mbar_wait(bars + 8 * (BAR_FULL + 1), 0);
      tile_step(d0, desc_x(b_x(7)), desc_w(b_w(7), 4));
      tile_step(dw, desc_x(b_x(4) + 1), desc_w(b_w(4)));
      Gelu<24> g0;
      g0.start(ep);
      wg_wait<1>();
      tile_step(dw, desc_x(b_x(5) + 1), desc_w(b_w(5)));
      g0.part<0, PS>(d0, r0, r1);
      pin(r0, r1, ep, gp.zero);
      wg_wait<1>();
      if (p < 4) mbar_arrive(ev_bar(bars, 30));
      tile_step(dw, desc_x(b_x(6) + 1), desc_w(b_w(6)));
      g0.part<PS, PS + PS2>(d0, r0, r1);
      pin(r0, r1, ep, gp.zero);
      wg_wait<1>();
      tile_step(dw, desc_x(b_x(7) + 1), desc_w(b_w(7), 4));
      g0.part<PS + PS2, 24>(d0, r0, r1);
      sts64f(sb + OFF_RS1 + p * 8, r0, r1);
      cin_begin(c, sb, 1, slot_of(1, 0), xA, accA, z);
      if (p < 4) mbar_arrive(ev_bar(bars, EV_END));
#pragma unroll
      for (int i = 0; i < 24; i++)
        sts128f(sb + p * 16 + (i < 16 ? OFF_PARK + i * 2048 : OFF_PARK2 + (i - 16) * 2048), dw[4 * i], dw[4 * i + 1], dw[4 * i + 2], dw[4 * i + 3]);
      __syncwarp();
      if (lane == 0) mbar_arrive(bars + 8 * BAR_PARK);
    }
    if (!role(1)) {
      cin_begin(c, sb, wg, OFF_GIDX + wg * XSLOT, xA, accA, z);
      sts128f(sb + OFF_RS0 + p * 16, r0, r1, r2, r3);
      __syncwarp();
      if (lane == 0) mbar_arrive(bars + 8 * BAR_PARK);
    }

    {
    int cta, tid;
    asm volatile("mov.u32 %0, %%ctaid.x;" : "=r"(cta));
    asm volatile("mov.u32 %0, %%tid.x;" : "=r"(tid));
    cta = __shfl_sync(0xffffffffu, cta, 0);
    const bool gemm = cta < NGEMM;
    const int p = tid & 127, wg = __shfl_sync(0xffffffffu, tid >> 7, 0);
    const int ncin = cin_count(cta);
    const int n0 = gemm ? NC_WG0 : NC_EXTRA / 2;
    const int rb = wg ? n0 : 0;
    const int nj = wg ? ncin - n0 : n0;
    cin_setup(c, sb, wg, p, gemm, nj, gp.zero);
    uint32_t fa = sb + (gemm ? slot_of(wg, (p >> 3) + 1) + NF * 128 : (wg ? XOFF_CIN1 : XOFF_CIN0) + (p >> 3) * CROW) + (p & 7) * 16, fd = sb + OFF_DNN + rb * 8;
    asm volatile("" : "+r"(fa), "+r"(fd));
    auto wg_sync = [&]() { if (wg == 0) bar_sync<1, 128>(); else bar_sync<3, 128>(); };
    auto result = [&](int r, bool on) {
      const uint32_t a = fa + (r & ~15) * CROW;
      const float4 v0 = lds128f(a), v1 = lds128f(a + 128), v2 = lds128f(a + 256), v3 = lds128f(a + 384);
      const int2 dn = lds64(fd + r * 8);
      float s = (((v0.x + v0.y) + (v0.z + v0.w)) + ((v1.x + v1.y) + (v1.z + v1.w))) +
                (((v2.x + v2.y) + (v2.z + v2.w)) + ((v3.x + v3.y) + (v3.z + v3.w)));
      s += __shfl_xor_sync(0xffffffffu, s, 1);
      s += __shfl_xor_sync(0xffffffffu, s, 2);
      s += __shfl_xor_sync(0xffffffffu, s, 4);
      if ((p & 7) == 0 && on) out[dn.y] = __float2bfloat16(s + __int_as_float(dn.x));
    };
    mbar_wait(gemm ? bars + 8 * BAR_GDONE : ev_bar(bars, EV_END), 0);
    cin_run(c, nj, xA, accA, z, [&]() {
      mbar_wait(bars + 8 * BAR_DNN, 0);
    }, [&](int j) {
    });
    wg_sync();
#pragma unroll 1
    for (int r = p >> 3; r < ((nj + 15) & ~15); r += 16) result(r, r < nj);
    }
  }
}

typedef CUresult (*EncodeFn)(CUtensorMap*, CUtensorMapDataType, cuuint32_t, void*, const cuuint64_t*, const cuuint64_t*,
                             const cuuint32_t*, const cuuint32_t*, CUtensorMapInterleave, CUtensorMapSwizzle,
                             CUtensorMapL2promotion, CUtensorMapFloatOOBfill);

extern "C" void kernel_launch(void* const* d_in, const int* in_sizes, int n_in, void* d_out, int out_size) {
  void* fn = nullptr;
  cudaDriverEntryPointQueryResult q;
  cudaGetDriverEntryPoint("cuTensorMapEncodeTiled", &fn, cudaEnableDefault, &q);
  EncodeFn enc = (EncodeFn)fn;
  CUtensorMap tmW, tmT, tmS, tmC;
  const cuuint32_t es[3] = {1, 1, 1};
  {
    cuuint64_t dims[2] = {DIN, DIN}, st[1] = {DIN * 2};
    cuuint32_t box[2] = {64, 64};
    enc(&tmW, CU_TENSOR_MAP_DATA_TYPE_BFLOAT16, 2, d_in[4], dims, st, box, es, CU_TENSOR_MAP_INTERLEAVE_NONE,
        CU_TENSOR_MAP_SWIZZLE_128B, CU_TENSOR_MAP_L2_PROMOTION_NONE, CU_TENSOR_MAP_FLOAT_OOB_FILL_NONE);
  }
  {
    cuuint64_t dims[2] = {64, (cuuint64_t)(in_sizes[1] / 64)}, st[1] = {128};
    cuuint32_t box[2] = {64, 1};
    enc(&tmT, CU_TENSOR_MAP_DATA_TYPE_BFLOAT16, 2, d_in[1], dims, st, box, es, CU_TENSOR_MAP_INTERLEAVE_NONE,
        CU_TENSOR_MAP_SWIZZLE_128B, CU_TENSOR_MAP_L2_PROMOTION_NONE, CU_TENSOR_MAP_FLOAT_OOB_FILL_NONE);
  }
  void* x0 = nullptr;
  cudaGetSymbolAddress(&x0, g_x0);
  {
    cuuint64_t dims[2] = {FS * 64, NB}, st[1] = {FS * 128};
    cuuint32_t box[2] = {64, NC_GEMM + 1};
    enc(&tmS, CU_TENSOR_MAP_DATA_TYPE_BFLOAT16, 2, x0, dims, st, box, es, CU_TENSOR_MAP_INTERLEAVE_NONE,
        CU_TENSOR_MAP_SWIZZLE_128B, CU_TENSOR_MAP_L2_PROMOTION_NONE, CU_TENSOR_MAP_FLOAT_OOB_FILL_NONE);
  }
  {
    cuuint64_t dims[2] = {64, NB * FS}, st[1] = {128};
    cuuint32_t box[2] = {64, FS};
    enc(&tmC, CU_TENSOR_MAP_DATA_TYPE_BFLOAT16, 2, x0, dims, st, box, es, CU_TENSOR_MAP_INTERLEAVE_NONE,
        CU_TENSOR_MAP_SWIZZLE_128B, CU_TENSOR_MAP_L2_PROMOTION_NONE, CU_TENSOR_MAP_FLOAT_OOB_FILL_NONE);
  }
  GPtr gp;
  gp.zero = 0;
  cudaGetSymbolAddress((void**)&gp.s, g_scratch);
  cudaGetSymbolAddress((void**)&gp.tab, g_slot_tab);
  cudaFuncSetAttribute(xdeepfm_kernel, cudaFuncAttributeMaxDynamicSharedMemorySize, SMEM_BYTES);
  xdeepfm_kernel<<<GRID, 384, SMEM_BYTES, cudaStreamPerThread>>>(
      (const int*)d_in[0], (const __nv_bfloat16*)d_in[1], (const __nv_bfloat16*)d_in[4], (const __nv_bfloat16*)d_in[5],
      (const __nv_bfloat16*)d_in[6], (const __nv_bfloat16*)d_in[2], (const __nv_bfloat16*)d_in[3],
      (const __nv_bfloat16*)d_in[7], (__nv_bfloat16*)d_out, gp, tmW, tmT, tmS, tmC);
}
```

```cpp
#include <cuda_runtime.h>
#include <cuda_bf16.h>
#include <cuda.h>
#include <stdint.h>

__device__ __forceinline__ void wgmma_ss_n256(float (&d)[96], float (&e)[32], uint64_t descA, uint64_t descB, int scaleD) {
  asm volatile("{\n.reg .pred p;\nsetp.ne.b32 p, %130, 0;\n"
      "wgmma.mma_async.sync.aligned.m64n256k16.f32.bf16.bf16 {"
      "%0, %1, %2, %3, %4, %5, %6, %7, %8, %9, %10, %11, %12, %13, %14, %15,"
      "%16, %17, %18, %19, %20, %21, %22, %23, %24, %25, %26, %27, %28, %29, %30, %31,"
      "%32, %33, %34, %35, %36, %37, %38, %39, %40, %41, %42, %43, %44, %45, %46, %47,"
      "%48, %49, %50, %51, %52, %53, %54, %55, %56, %57, %58, %59, %60, %61, %62, %63,"
      "%64, %65, %66, %67, %68, %69, %70, %71, %72, %73, %74, %75, %76, %77, %78, %79,"
      "%80, %81, %82, %83, %84, %85, %86, %87, %88, %89, %90, %91, %92, %93, %94, %95,"
      "%96, %97, %98, %99, %100, %101, %102, %103, %104, %105, %106, %107, %108, %109, %110, %111,"
      "%112, %113, %114, %115, %116, %117, %118, %119, %120, %121, %122, %123, %124, %125, %126, %127"
      "}, %128, %129, p, 1, 1, 0, 1;\n}\n"
      : "+f"(d[0]), "+f"(d[1]), "+f"(d[2]), "+f"(d[3]), "+f"(d[4]), "+f"(d[5]), "+f"(d[6]), "+f"(d[7]),
        "+f"(d[8]), "+f"(d[9]), "+f"(d[10]), "+f"(d[11]), "+f"(d[12]), "+f"(d[13]), "+f"(d[14]), "+f"(d[15]),
        "+f"(d[16]), "+f"(d[17]), "+f"(d[18]), "+f"(d[19]), "+f"(d[20]), "+f"(d[21]), "+f"(d[22]), "+f"(d[23]),
        "+f"(d[24]), "+f"(d[25]), "+f"(d[26]), "+f"(d[27]), "+f"(d[28]), "+f"(d[29]), "+f"(d[30]), "+f"(d[31]),
        "+f"(d[32]), "+f"(d[33]), "+f"(d[34]), "+f"(d[35]), "+f"(d[36]), "+f"(d[37]), "+f"(d[38]), "+f"(d[39]),
        "+f"(d[40]), "+f"(d[41]), "+f"(d[42]), "+f"(d[43]), "+f"(d[44]), "+f"(d[45]), "+f"(d[46]), "+f"(d[47]),
        "+f"(d[48]), "+f"(d[49]), "+f"(d[50]), "+f"(d[51]), "+f"(d[52]), "+f"(d[53]), "+f"(d[54]), "+f"(d[55]),
        "+f"(d[56]), "+f"(d[57]), "+f"(d[58]), "+f"(d[59]), "+f"(d[60]), "+f"(d[61]), "+f"(d[62]), "+f"(d[63]),
        "+f"(d[64]), "+f"(d[65]), "+f"(d[66]), "+f"(d[67]), "+f"(d[68]), "+f"(d[69]), "+f"(d[70]), "+f"(d[71]),
        "+f"(d[72]), "+f"(d[73]), "+f"(d[74]), "+f"(d[75]), "+f"(d[76]), "+f"(d[77]), "+f"(d[78]), "+f"(d[79]),
        "+f"(d[80]), "+f"(d[81]), "+f"(d[82]), "+f"(d[83]), "+f"(d[84]), "+f"(d[85]), "+f"(d[86]), "+f"(d[87]),
        "+f"(d[88]), "+f"(d[89]), "+f"(d[90]), "+f"(d[91]), "+f"(d[92]), "+f"(d[93]), "+f"(d[94]), "+f"(d[95]),
        "+f"(e[0]), "+f"(e[1]), "+f"(e[2]), "+f"(e[3]), "+f"(e[4]), "+f"(e[5]), "+f"(e[6]), "+f"(e[7]),
        "+f"(e[8]), "+f"(e[9]), "+f"(e[10]), "+f"(e[11]), "+f"(e[12]), "+f"(e[13]), "+f"(e[14]), "+f"(e[15]),
        "+f"(e[16]), "+f"(e[17]), "+f"(e[18]), "+f"(e[19]), "+f"(e[20]), "+f"(e[21]), "+f"(e[22]), "+f"(e[23]),
        "+f"(e[24]), "+f"(e[25]), "+f"(e[26]), "+f"(e[27]), "+f"(e[28]), "+f"(e[29]), "+f"(e[30]), "+f"(e[31])
      : "l"(descA), "l"(descB), "r"(scaleD));
}
__device__ __forceinline__ void wgmma_ss_n192(float (&d)[96], uint64_t descA, uint64_t descB, int scaleD) {
  asm volatile("{\n.reg .pred p;\nsetp.ne.b32 p, %98, 0;\n"
      "wgmma.mma_async.sync.aligned.m64n192k16.f32.bf16.bf16 {"
      "%0, %1, %2, %3, %4, %5, %6, %7, %8, %9, %10, %11, %12, %13, %14, %15,"
      "%16, %17, %18, %19, %20, %21, %22, %23, %24, %25, %26, %27, %28, %29, %30, %31,"
      "%32, %33, %34, %35, %36, %37, %38, %39, %40, %41, %42, %43, %44, %45, %46, %47,"
      "%48, %49, %50, %51, %52, %53, %54, %55, %56, %57, %58, %59, %60, %61, %62, %63,"
      "%64, %65, %66, %67, %68, %69, %70, %71, %72, %73, %74, %75, %76, %77, %78, %79,"
      "%80, %81, %82, %83, %84, %85, %86, %87, %88, %89, %90, %91, %92, %93, %94, %95"
      "}, %96, %97, p, 1, 1, 0, 1;\n}\n"
      : "+f"(d[0]), "+f"(d[1]), "+f"(d[2]), "+f"(d[3]), "+f"(d[4]), "+f"(d[5]), "+f"(d[6]), "+f"(d[7]),
        "+f"(d[8]), "+f"(d[9]), "+f"(d[10]), "+f"(d[11]), "+f"(d[12]), "+f"(d[13]), "+f"(d[14]), "+f"(d[15]),
        "+f"(d[16]), "+f"(d[17]), "+f"(d[18]), "+f"(d[19]), "+f"(d[20]), "+f"(d[21]), "+f"(d[22]), "+f"(d[23]),
        "+f"(d[24]), "+f"(d[25]), "+f"(d[26]), "+f"(d[27]), "+f"(d[28]), "+f"(d[29]), "+f"(d[30]), "+f"(d[31]),
        "+f"(d[32]), "+f"(d[33]), "+f"(d[34]), "+f"(d[35]), "+f"(d[36]), "+f"(d[37]), "+f"(d[38]), "+f"(d[39]),
        "+f"(d[40]), "+f"(d[41]), "+f"(d[42]), "+f"(d[43]), "+f"(d[44]), "+f"(d[45]), "+f"(d[46]), "+f"(d[47]),
        "+f"(d[48]), "+f"(d[49]), "+f"(d[50]), "+f"(d[51]), "+f"(d[52]), "+f"(d[53]), "+f"(d[54]), "+f"(d[55]),
        "+f"(d[56]), "+f"(d[57]), "+f"(d[58]), "+f"(d[59]), "+f"(d[60]), "+f"(d[61]), "+f"(d[62]), "+f"(d[63]),
        "+f"(d[64]), "+f"(d[65]), "+f"(d[66]), "+f"(d[67]), "+f"(d[68]), "+f"(d[69]), "+f"(d[70]), "+f"(d[71]),
        "+f"(d[72]), "+f"(d[73]), "+f"(d[74]), "+f"(d[75]), "+f"(d[76]), "+f"(d[77]), "+f"(d[78]), "+f"(d[79]),
        "+f"(d[80]), "+f"(d[81]), "+f"(d[82]), "+f"(d[83]), "+f"(d[84]), "+f"(d[85]), "+f"(d[86]), "+f"(d[87]),
        "+f"(d[88]), "+f"(d[89]), "+f"(d[90]), "+f"(d[91]), "+f"(d[92]), "+f"(d[93]), "+f"(d[94]), "+f"(d[95])
      : "l"(descA), "l"(descB), "r"(scaleD));
}
template <unsigned long long DESC, int SCALE>
__device__ __forceinline__ void wgmma_rs_n56(float (&d)[28], uint32_t a0, uint32_t a1, uint32_t a2, uint32_t a3) {
  asm volatile("{\n.reg .b64 desc;\nmov.b64 desc, %32;\n"
      "wgmma.mma_async.sync.aligned.m64n56k16.f32.bf16.bf16 {"
      "%0, %1, %2, %3, %4, %5, %6, %7, %8, %9, %10, %11, %12, %13, %14, %15,"
      "%16, %17, %18, %19, %20, %21, %22, %23, %24, %25, %26, %27"
      "}, {%28, %29, %30, %31}, desc, %33, 1, 1, 0;\n}\n"
      : "+f"(d[0]), "+f"(d[1]), "+f"(d[2]), "+f"(d[3]), "+f"(d[4]), "+f"(d[5]), "+f"(d[6]), "+f"(d[7]),
        "+f"(d[8]), "+f"(d[9]), "+f"(d[10]), "+f"(d[11]), "+f"(d[12]), "+f"(d[13]), "+f"(d[14]), "+f"(d[15]),
        "+f"(d[16]), "+f"(d[17]), "+f"(d[18]), "+f"(d[19]), "+f"(d[20]), "+f"(d[21]), "+f"(d[22]), "+f"(d[23]),
        "+f"(d[24]), "+f"(d[25]), "+f"(d[26]), "+f"(d[27])
      : "r"(a0), "r"(a1), "r"(a2), "r"(a3), "n"(DESC), "n"(SCALE));
}
template <unsigned long long DESC, int SCALE>
__device__ __forceinline__ void wgmma_rs_n32(float (&d)[28], uint32_t a0, uint32_t a1, uint32_t a2, uint32_t a3) {
  asm volatile("{\n.reg .b64 desc;\nmov.b64 desc, %20;\n"
      "wgmma.mma_async.sync.aligned.m64n32k16.f32.bf16.bf16 {"
      "%0, %1, %2, %3, %4, %5, %6, %7, %8, %9, %10, %11, %12, %13, %14, %15"
      "}, {%16, %17, %18, %19}, desc, %21, 1, 1, 0;\n}\n"
      : "+f"(d[0]), "+f"(d[1]), "+f"(d[2]), "+f"(d[3]), "+f"(d[4]), "+f"(d[5]), "+f"(d[6]), "+f"(d[7]),
        "+f"(d[8]), "+f"(d[9]), "+f"(d[10]), "+f"(d[11]), "+f"(d[12]), "+f"(d[13]), "+f"(d[14]), "+f"(d[15])
      : "r"(a0), "r"(a1), "r"(a2), "r"(a3), "n"(DESC), "n"(SCALE));
}

constexpr int NB = 4096, NF = 26, DIN = 1664;
constexpr int NGEMM = 128, NEXTRA = 4, GRID = NGEMM + NEXTRA;
constexpr int NC_EXTRA = 84;
constexpr int NC_WG0 = 16;
constexpr int HK = 4;
constexpr int PE0 = 9;
constexpr int WD = 2;
constexpr int GI = 3;
constexpr int PE1 = 4;
constexpr int PE2 = 8;
constexpr int PS2 = 6;
constexpr int POLL = 400;
constexpr int BGN = 1;
constexpr int PREG = 48;
constexpr int PS = 6;
constexpr int RB = 4;
constexpr int NC_GEMM = 29, NBIG = NB - NGEMM * NC_GEMM - NEXTRA * NC_EXTRA;
static_assert(NBIG >= 0 && NBIG <= NGEMM && NC_EXTRA % 4 == 0 && NC_EXTRA <= 96, "split");
constexpr int CW_MAIN = 22 * 1792, CW_LIN = 2 * 1024, CW_BYTES = CW_MAIN + CW_LIN;
constexpr int XSLOT = 4096;

constexpr int UNIT = 8192, FS = 18;
constexpr int U_W = 6, U_XB = 18, U_SP = 24;
constexpr int CW_CUT = 9;
constexpr int OFF_CW = 0, OFF_CW2 = 6 * UNIT, OFF_CWL = 9 * UNIT;
constexpr int CROW = 528;
constexpr int OFF_PARK = 10 * UNIT, OFF_PARK2 = 24 * UNIT;
constexpr int OFF_RS0 = OFF_CWL + CW_LIN, OFF_RS1 = OFF_CWL - 1024;
constexpr int OFF_GIDX = 26 * UNIT;
constexpr int OFF_TIDX = OFF_GIDX + 128 * NF * 4 - 8 * 64 * 4;
constexpr int OFF_CIDX = OFF_GIDX + 128 * NF * 4;
constexpr int OFF_EPI = OFF_CIDX + 32 * 8 * 4;
constexpr int OFF_DNN = OFF_EPI + 128 * 16;
constexpr int OFF_BAR = OFF_DNN + 112 * 8;
constexpr int SMEM_BYTES = OFF_BAR + 50 * 8;
static_assert(CW_CUT * 1792 <= 2 * UNIT && (22 - CW_CUT) * 1792 <= 3 * UNIT , "smem");
constexpr uint32_t SMEM_BASE = 1024;
static_assert(SMEM_BYTES <= 232448, "smem");
static_assert(OFF_EPI % 16 == 0 && OFF_BAR % 8 == 0, "align");
constexpr int XOFF_W3 = 0, XOFF_W2 = 35152, XOFF_W1 = 70304, XOFF_M = XOFF_W1 + 8 * 1352, XOFF_S = XOFF_M + 32 * 40 * 4,
              XOFF_SLOT = 10 * UNIT, XOFF_CIN0 = 2 * UNIT, XOFF_CIN1 = 18 * UNIT, XOFF_CIDX = 22 * UNIT,
              XOFF_BAR = 24 * UNIT, NPAIR = NC_EXTRA / 4;
static_assert(XOFF_S + 14 * 3136 <= 21 * UNIT && 48 * CROW <= 4 * UNIT, "smem");

constexpr int BAR_PARK = 7,
              BAR_FULL = 8,
              BAR_EV = 16,
              BAR_CW = 24,
              BAR_GIDX = 25,
              BAR_X0 = 26,
              BAR_W0 = 27,
              BAR_DNN = 28,
              BAR_T = 29,
              BAR_GDONE = 30,
              BAR_EPOCH = 31,
              BAR_CFULL = 32,
              BAR_C0 = 48;
constexpr int EV_CW = 29, EV_SLOT = 30, EV_END = 33;
__device__ __forceinline__ uint32_t ev_bar(uint32_t bars, int e) { return bars + 8 * (BAR_EV + (e & 7)); }
__device__ __forceinline__ uint32_t ev_par(int e) { return (e >> 3) & 1; }
constexpr unsigned long long STAGES = 0xb4b4924924924ull;
__host__ __device__ constexpr int b_x(int t) { return ((0xb2c1430bu >> (4 * t)) & 15) * 2; }
__host__ __device__ constexpr int b_w(int t) { return (0x0d0a120eu >> (8 * (t & 3))) & 31; }
__host__ __device__ constexpr int b_ws(int t) { return (t & 3) == 3 ? 4 : 1; }

struct Scratch {
  uint4 cw[CW_BYTES / 16];
  uint2 part[8 * NB];
  unsigned epoch[GRID];
  unsigned foldflag;
};
__device__ __align__(128) Scratch g_scratch;
__device__ __align__(1024) __nv_bfloat16 g_x0[NB * FS * 64];
struct GPtr { Scratch* s; const uint4* tab; uint32_t zero; };

__device__ __forceinline__ void wg_fence() { asm volatile("wgmma.fence.sync.aligned;" ::: "memory"); }
__device__ __forceinline__ void wg_commit() { asm volatile("wgmma.commit_group.sync.aligned;" ::: "memory"); }
template <int N> __device__ __forceinline__ void wg_wait() { asm volatile("wgmma.wait_group.sync.aligned %0;" ::"n"(N) : "memory"); }
__device__ __forceinline__ uint64_t mkdesc(uint32_t addr, uint32_t lbo, uint32_t sbo, uint32_t swz) {
  return (uint64_t)((addr & 0x3FFFF) >> 4) | ((uint64_t)(lbo >> 4) << 16) | ((uint64_t)(sbo >> 4) << 32) | ((uint64_t)swz << 62);
}
__device__ __forceinline__ bool elect1() {
  uint32_t p; asm volatile("{\n.reg .pred p;\nelect.sync _|p, 0xffffffff;\nselp.b32 %0, 1, 0, p;\n}" : "=r"(p)); return p;
}
__device__ __forceinline__ int fresh(int v) { asm volatile("" : "+r"(v)); return v; }
__device__ __forceinline__ void mbar_init(uint32_t bar, uint32_t cnt) { asm volatile("mbarrier.init.shared::cta.b64 [%0], %1;" ::"r"(bar), "r"(cnt) : "memory"); }
__device__ __forceinline__ void mbar_arrive(uint32_t bar) { asm volatile("mbarrier.arrive.shared::cta.b64 _, [%0];" ::"r"(bar) : "memory"); }
__device__ __forceinline__ void mbar_arrive_cta(uint32_t bar, uint32_t cta) {
  asm volatile("{\n.reg .b32 r;\nmapa.shared::cluster.u32 r, %0, %1;\nmbarrier.arrive.shared::cluster.b64 _, [r];\n}" ::"r"(bar), "r"(cta) : "memory");
}
__device__ __forceinline__ void mbar_expect_tx(uint32_t bar, uint32_t bytes) { asm volatile("mbarrier.arrive.expect_tx.shared::cta.b64 _, [%0], %1;" ::"r"(bar), "r"(bytes) : "memory"); }
__device__ __forceinline__ void mbar_wait(uint32_t bar, uint32_t parity) {
  asm volatile("{\n.reg .pred p;\n.reg .u32 n;\n"
               "mbarrier.try_wait.parity.shared::cta.b64 p, [%0], %1;\n"
               "@p bra DONE;\n"
               "mov.u32 n, 0;\nLAB_WAIT:\n"
               "mbarrier.try_wait.parity.shared::cta.b64 p, [%0], %1;\n"
               "@p bra DONE;\n"
               "add.u32 n, n, 1;\n"
               "setp.lt.u32 p, n, 400000;\n"
               "@p bra LAB_WAIT;\n"
               "DONE:\n}" ::"r"(bar), "r"(parity) : "memory");
}
__device__ __forceinline__ void flag_wait(const unsigned* p, unsigned target, unsigned sleep_ns) {
  asm volatile("{\n.reg .pred p;\n.reg .u32 n, v;\nmov.u32 n, 0;\nLAB_WAIT:\n"
               "ld.acquire.gpu.global.u32 v, [%0];\n"
               "sub.u32 v, v, %1;\n"
               "setp.ge.s32 p, v, 0;\n"
               "@p bra DONE;\n"
               "nanosleep.u32 %2;\n"
               "add.u32 n, n, 1;\n"
               "setp.lt.u32 p, n, 400000;\n"
               "@p bra LAB_WAIT;\n"
               "DONE:\n}" ::"l"(p), "r"(target), "r"(sleep_ns) : "memory");
}
__device__ __forceinline__ void put_tagged(uint2* p, float v, unsigned tag) {
  asm volatile("st.relaxed.gpu.global.v2.b32 [%0], {%1, %2};" ::"l"(p), "r"(__float_as_uint(v)), "r"(tag) : "memory");
}
__device__ __forceinline__ void flag_add(unsigned* p) { asm volatile("red.release.gpu.global.add.u32 [%0], 1;" ::"l"(p) : "memory"); }
__device__ __forceinline__ void tma_load(uint32_t dst, const CUtensorMap* tm, int c0, int c1, uint32_t bar) {
  asm volatile("cp.async.bulk.tensor.2d.shared::cluster.global.mbarrier::complete_tx::bytes [%0], [%1, {%3, %4}], [%2];"
               ::"r"(dst), "l"(tm), "r"(bar), "r"(c0), "r"(c1) : "memory");
}
__device__ __forceinline__ void tma_row_mc(uint32_t dst, const CUtensorMap* tm, int row, uint32_t bar) {
  asm volatile("cp.async.bulk.tensor.2d.shared::cluster.global.mbarrier::complete_tx::bytes.multicast::cluster [%0], [%1, {%3, %4}], [%2], %5;"
               ::"r"(dst), "l"(tm), "r"(bar), "r"(0), "r"(row), "h"((uint16_t)3));
}
__device__ __forceinline__ void tma_row(uint32_t dst, const CUtensorMap* tm, int row, uint32_t bar) {
  asm volatile("cp.async.bulk.tensor.2d.shared::cluster.global.mbarrier::complete_tx::bytes [%0], [%1, {%3, %4}], [%2];"
               ::"r"(dst), "l"(tm), "r"(bar), "r"(0), "r"(row));
}
__device__ __forceinline__ void tma_store(const CUtensorMap* tm, int c0, int c1, uint32_t src) {
  asm volatile("cp.async.bulk.tensor.2d.global.shared::cta.bulk_group [%0, {%1, %2}], [%3];\ncp.async.bulk.commit_group;"
               ::"l"(tm), "r"(c0), "r"(c1), "r"(src) : "memory");
}
template <int N> __device__ __forceinline__ void store_read() { asm volatile("cp.async.bulk.wait_group.read %0;" ::"n"(N) : "memory"); }
__device__ __forceinline__ void bulk_load(uint32_t dst, const void* src, uint32_t bytes, uint32_t bar) {
  asm volatile("cp.async.bulk.shared::cluster.global.mbarrier::complete_tx::bytes [%0], [%1], %2, [%3];"
               ::"r"(dst), "l"(src), "r"(bytes), "r"(bar));
}
__device__ __forceinline__ void l2_prefetch(const void* src, uint32_t bytes) {
  asm volatile("cp.async.bulk.prefetch.L2.global [%0], %1;" ::"l"(src), "r"(bytes));
}
__device__ __forceinline__ void w_prefetch(const __nv_bfloat16* w1, int f, int cta, int piece) {
  l2_prefetch(w1 + (f * 64 + (cta >> 3) * 4 + (cta & 1) * 2 + (piece & 1)) * DIN + (piece < 2 ? (cta & 6) * 192 : 1536 + (cta & 4) * 16),
              piece < 2 ? 768 : 128);
}
__device__ __forceinline__ void cpasync16(uint32_t dst, const void* src) {
  asm volatile("cp.async.cg.shared.global [%0], [%1], 16;" ::"r"(dst), "l"(src) : "memory");
}
template <int ID, int N> __device__ __forceinline__ void bar_sync() { asm volatile("bar.sync %0, %1;" ::"n"(ID), "n"(N) : "memory"); }
template <int ID, int N> __device__ __forceinline__ void bar_arrive() { asm volatile("bar.arrive %0, %1;" ::"n"(ID), "n"(N) : "memory"); }
__device__ __forceinline__ void ldsm4t(uint32_t& a, uint32_t& b, uint32_t& c, uint32_t& d, uint32_t addr) {
  asm volatile("ldmatrix.sync.aligned.m8n8.x4.trans.shared.b16 {%0,%1,%2,%3}, [%4];" : "=r"(a), "=r"(b), "=r"(c), "=r"(d) : "r"(addr) : "memory");
}
__device__ __forceinline__ int lds32(uint32_t addr) { int v; asm volatile("ld.shared.b32 %0, [%1];" : "=r"(v) : "r"(addr)); return v; }
__device__ __forceinline__ int2 lds64(uint32_t addr) { int2 v; asm volatile("ld.shared.v2.b32 {%0,%1}, [%2];" : "=r"(v.x), "=r"(v.y) : "r"(addr)); return v; }
__device__ __forceinline__ int4 lds128(uint32_t addr) {
  int4 v; asm volatile("ld.shared.v4.b32 {%0,%1,%2,%3}, [%4];" : "=r"(v.x), "=r"(v.y), "=r"(v.z), "=r"(v.w) : "r"(addr)); return v;
}
__device__ __forceinline__ float4 lds128f(uint32_t addr) {
  float4 v; asm volatile("ld.shared.v4.f32 {%0,%1,%2,%3}, [%4];" : "=f"(v.x), "=f"(v.y), "=f"(v.z), "=f"(v.w) : "r"(addr) : "memory"); return v;
}
__device__ __forceinline__ float4 lds128f(uint32_t addr, uint32_t off) {
  float4 v;
  asm volatile("{\n.reg .u32 t;\nadd.u32 t, %4, %5;\nld.shared.v4.f32 {%0,%1,%2,%3}, [t];\n}" : "=f"(v.x), "=f"(v.y), "=f"(v.z), "=f"(v.w) : "r"(addr), "r"(off) : "memory");
  return v;
}
__device__ __forceinline__ void sts32f(uint32_t addr, float v) { asm volatile("st.shared.f32 [%0], %1;" ::"r"(addr), "f"(v) : "memory"); }
__device__ __forceinline__ float bf_lo(uint32_t v) { return __uint_as_float(v << 16); }
__device__ __forceinline__ float bf_hi(uint32_t v) { return __uint_as_float(v & 0xffff0000u); }
__device__ __forceinline__ float bf2f(__nv_bfloat16 v) { return __bfloat162float(v); }

__device__ __forceinline__ uint32_t mul2(uint32_t a, uint32_t b) {
  uint32_t r; asm volatile("mul.rn.bf16x2 %0, %1, %2;" : "=r"(r) : "r"(a), "r"(b)); return r;
}
__device__ __forceinline__ uint32_t mul2lo(uint32_t a, uint32_t b) {
  uint32_t r;
  asm volatile("{\n.reg .b16 l, h;\n.reg .b32 t;\nmov.b32 {l, h}, %2;\nmov.b32 t, {l, l};\nmul.rn.bf16x2 %0, %1, t;\n}" : "=r"(r) : "r"(a), "r"(b));
  return r;
}
__device__ __forceinline__ uint32_t mul2hi(uint32_t a, uint32_t b) {
  uint32_t r;
  asm volatile("{\n.reg .b16 l, h;\n.reg .b32 t;\nmov.b32 {l, h}, %2;\nmov.b32 t, {h, h};\nmul.rn.bf16x2 %0, %1, t;\n}" : "=r"(r) : "r"(a), "r"(b));
  return r;
}

__host__ __device__ constexpr int xfield(int r, int e, int c) {
  return r == 9 ? 24 + e : 8 * (r / 3) + 2 * (((r % 3) + c) & 3) + (((r % 3) == 2 && c >= 2) ? 1 - e : e);
}
__host__ __device__ constexpr int blk_a(int b) { return b < 12 ? 3 * (b / 8) + ((b & 3) == 3) : (b < 15 ? 3 * (b - 12) : 3 * (b - 15)); }
__host__ __device__ constexpr int blk_b(int b) { return b < 12 ? 3 * (b < 4 ? 1 : 2) + ((b & 3) == 3 ? 0 : (b & 3)) : (b < 15 ? 3 * (b - 12) + 1 : 9); }
__host__ __device__ constexpr int slot_pq(int u, int e, int c) {
  return u < 36 ? (xfield(blk_a(u >> 1), e, c) | (xfield(blk_b(u >> 1), u & 1, c) << 8))
       : u < 39 ? (xfield(3 * (u - 36), e, c) * 257)
       : u < 42 ? (xfield(3 * (u - 39), e, c) | (xfield(3 * (u - 39) + 2, e, c) << 8))
       : u == 42 ? (xfield(3 * e, 0, c) | (xfield(3 * e, 1, c) << 8))
       : u == 43 ? (e == 0 ? (xfield(6, 0, c) | (xfield(6, 1, c) << 8))
                           : (c == 0 ? 24 * 257 : c == 1 ? 25 * 257 : c == 2 ? (24 | 25 << 8) : 26 * 257))
       : u < 47 ? (xfield(3 * (u - 44), e, c) | (26 << 8))
       : (c == 0 ? ((24 + e) | 26 << 8) : 27 * 257);
}
struct SlotTab { uint32_t v[48 * 8]; };
constexpr SlotTab make_slot_tab() {
  SlotTab t{};
  for (int u = 0; u < 48; u++)
    for (int k = 0; k < 8; k++) {
      const int pq = slot_pq(u, k & 1, k >> 1), p = pq & 255, q = pq >> 8;
      t.v[u * 8 + k] = (uint32_t)((p * 28 + q) * 4) | ((uint32_t)(((p != q && q < 26) ? q * 28 + p : 27 * 28 + 27) * 4) << 16);
    }
  return t;
}
__device__ __align__(16) const SlotTab g_slot_tab = make_slot_tab();

struct CinCtx {
  uint32_t o03, o14, o25, o69, o78, cin, selA, selB;
  bool ones, lead;
  uint32_t so, so2, co, co2, bar, jump, dslot, last;
  bool ring;
};
constexpr unsigned long long CW_DESC = (unsigned long long)((SMEM_BASE + OFF_CW) >> 4) | (8ull << 16) | (16ull << 32);
constexpr unsigned long long CWL_DESC = CW_DESC + (OFF_CWL - OFF_CW) / 16;

template <int U>
__device__ __forceinline__ uint32_t zreg(const uint32_t (&x)[10][2], int h, const CinCtx& c) {
  if constexpr (U < 36) {
    if constexpr (U & 1) return mul2hi(x[blk_a(U >> 1)][h], x[blk_b(U >> 1)][h]);
    else return mul2lo(x[blk_a(U >> 1)][h], x[blk_b(U >> 1)][h]);
  } else if constexpr (U < 39) {
    return mul2(x[3 * (U - 36)][h], x[3 * (U - 36)][h]);
  } else if constexpr (U < 42) {
    return mul2(x[3 * (U - 39)][h], x[3 * (U - 39) + 2][h]);
  } else if constexpr (U == 42) {
    return mul2(__byte_perm(x[0][h], x[3][h], 0x5410), __byte_perm(x[0][h], x[3][h], 0x7632));
  } else {
    const uint32_t f = c.ones ? 0x3f803f80u : x[9][h];
    return mul2(__byte_perm(x[6][h], f, c.selA), __byte_perm(x[6][h], f, c.selB));
  }
}

template <int G>
__device__ __forceinline__ void z_fill(uint32_t (&z)[8], const uint32_t (&x)[10][2], const CinCtx& c) {
  z[0] = zreg<4 * G>(x, 0, c);     z[1] = zreg<4 * G>(x, 1, c);
  z[2] = zreg<4 * G + 1>(x, 0, c); z[3] = zreg<4 * G + 1>(x, 1, c);
  z[4] = zreg<4 * G + 2>(x, 0, c); z[5] = zreg<4 * G + 2>(x, 1, c);
  z[6] = zreg<4 * G + 3>(x, 0, c); z[7] = zreg<4 * G + 3>(x, 1, c);
}
__host__ __device__ constexpr unsigned long long cw_desc(int s) { return CW_DESC + (s < CW_CUT ? s * 1792 : OFF_CW2 - OFF_CW + (s - CW_CUT) * 1792) / 16; }
template <int G>
__device__ __forceinline__ void z_mma(float (&acc)[28], const uint32_t (&z)[8]) {
  wgmma_rs_n56<cw_desc(2 * G), G != 0>(acc, z[0], z[1], z[2], z[3]);
  wgmma_rs_n56<cw_desc(2 * G + 1), 1>(acc, z[4], z[5], z[6], z[7]);
}

__device__ __forceinline__ void cin_finish(const CinCtx& c, float (&acc)[28], uint32_t out) {
#pragma unroll
  for (int i = 0; i < 28; i++) asm volatile("" : "+f"(acc[i]));
  float s0 = acc[12] * acc[13], s1 = acc[14] * acc[15];
#pragma unroll
  for (int i = 0; i < 12; i += 2) {
    s0 = fmaf(acc[i], acc[16 + i], s0);
    s1 = fmaf(acc[i + 1], acc[17 + i], s1);
  }
  sts32f(c.cin + out, s0 + s1);
}

__device__ __forceinline__ void cin_ldsm(const CinCtx& c, uint32_t so, uint32_t (&x)[10][2]) {
  ldsm4t(x[0][0], x[0][1], x[3][0], x[3][1], so + c.o03);
  ldsm4t(x[1][0], x[1][1], x[4][0], x[4][1], so + c.o14);
  ldsm4t(x[2][0], x[2][1], x[5][0], x[5][1], so + c.o25);
  ldsm4t(x[6][0], x[6][1], x[9][0], x[9][1], so + c.o69);
  ldsm4t(x[7][0], x[7][1], x[8][0], x[8][1], so + c.o78);
}
__device__ __forceinline__ void cin_load(const CinCtx& c, int k, bool real, uint32_t (&x)[10][2]) {
  if (k == 0 && real) mbar_wait(c.bar, 0);
  cin_ldsm(c, k ? c.so2 : c.so, x);
  if (k == 1 && c.lead) mbar_arrive(c.bar + 8 * NPAIR);
}
__device__ __forceinline__ void cin_advance(CinCtx& c) {
  const uint32_t d = c.so == c.jump ? c.dslot : 2 * XSLOT;
  c.so += d; c.so2 += d;
  c.co = c.ring ? c.co + 2 * CROW : c.so;
  c.bar += 8;
}
constexpr int CG_WAIT = 2;
constexpr int CG_FIN = 2;
constexpr int CG_HEAD = 3;
constexpr int CG_LIN = 3;
constexpr int CG_LOAD = 5;
constexpr int CG_N = 11;
static_assert(CG_FIN >= CG_WAIT && CG_FIN < CG_HEAD && CG_LOAD >= CG_HEAD && CG_LIN >= CG_HEAD && CG_LOAD < 10, "CIN schedule");
template <int G, int GEND, typename F>
__device__ __forceinline__ void cin_groups(const CinCtx& c, const uint32_t (&x)[10][2], float (&acc)[28], uint32_t (&z)[8],
                                           int q, bool more, uint32_t (&xn)[10][2], F finish) {
  if constexpr (G < GEND) {
    wg_fence();
    if constexpr (G == CG_LIN) {
      wgmma_rs_n32<CWL_DESC, 1>(acc, x[0][0], x[0][1], x[3][0], x[3][1]);
      wgmma_rs_n32<CWL_DESC + 1024 / 16, 1>(acc, x[6][0], x[6][1], x[9][0], x[9][1]);
    }
    z_mma<G>(acc, z);
    wg_commit();
    if constexpr (G == CG_LOAD) cin_load(c, q, more, xn);
    uint32_t zn[8];
    if constexpr (G + 1 < CG_N) z_fill<G + 1>(zn, x, c); else z_fill<0>(zn, xn, c);
    if constexpr (G == CG_FIN) finish();
    wg_wait<CG_WAIT>();
    if constexpr (G + 1 < GEND) cin_groups<G + 1, GEND>(c, x, acc, zn, q, more, xn, finish);
    else {
#pragma unroll
      for (int i = 0; i < 8; i++) z[i] = zn[i];
    }
    if constexpr (G + 1 < GEND) {
#pragma unroll
      for (int i = 0; i < 8; i++) z[i] = zn[i];
    }
  }
}
template <typename F>
__device__ __forceinline__ void cin_head(const CinCtx& c, uint32_t (&x)[10][2], float (&acc)[28], uint32_t (&z)[8], F finish) {
  cin_groups<0, CG_HEAD>(c, x, acc, z, 0, false, x, finish);
}
__device__ __forceinline__ void cin_tail(const CinCtx& c, const uint32_t (&x)[10][2], float (&acc)[28], uint32_t (&z)[8],
                                         int q, bool more, uint32_t (&xn)[10][2]) {
  cin_groups<CG_HEAD, CG_N>(c, x, acc, z, q, more, xn, []() {});
}

__device__ __forceinline__ int slot_of(int wg, int j) {
  return wg ? (j == 0 ? 9 * UNIT + XSLOT : j <= 8 ? 2 * UNIT + (j - 1) * XSLOT : 21 * UNIT + (j - 9) * XSLOT)
            : (j < 3 ? OFF_GIDX + j * XSLOT : 14 * UNIT + (j - 3) * XSLOT);
}

__device__ __forceinline__ void cin_begin(CinCtx& c, uint32_t sb, int wg, uint32_t first, uint32_t (&x)[10][2], float (&acc)[28], uint32_t (&z)[8]) {
  int t; asm volatile("mov.u32 %0, %%tid.x;" : "=r"(t));
  const int m = t & 16, f0 = t & 7, f1 = (f0 + 2) & 7, f2 = (f0 ^ 4) ^ (f0 >> 2);
  const uint32_t base = sb + m * 64, ch = (t & 96) + (t & 8) * 2;
  c.o03 = (base + f0 * 0x90) ^ ch;
  c.o14 = (base + f1 * 0x90) ^ ch;
  c.o25 = (base + f2 * 0x90) ^ ch;
  c.o69 = (base + 2048 + (m ? f0 & 1 : f0) * 0x90) ^ ch;
  c.o78 = m ? c.o25 + 1024 : c.o14 + 2048;
  mbar_wait(sb + OFF_BAR + 8 * BAR_GDONE, 0);
  mbar_wait(sb + OFF_BAR + 8 * (BAR_C0 + wg), 0);
  cin_ldsm(c, first, x);
  mbar_wait(sb + OFF_BAR + 8 * BAR_CW, 0);
  z_fill<0>(z, x, c);
  cin_head(c, x, acc, z, []() {});
}
__device__ __forceinline__ void cin_setup(CinCtx& c, uint32_t sb, int wg, int p, bool gemm, int nj, uint32_t zero) {
  c.bar = sb + (gemm ? OFF_BAR + 8 * (BAR_CFULL + wg * 8) : XOFF_BAR + wg * 16 * NPAIR);
  c.lead = (p & 31) == 0 && !gemm; c.ring = !gemm;
  c.so = !gemm ? XOFF_SLOT + 8 * wg * XSLOT : wg ? 2 * UNIT : OFF_GIDX + XSLOT;
  c.jump = c.so + (gemm && !wg ? 0 : 6 * XSLOT);
  c.dslot = !gemm ? -6 * XSLOT : wg ? 19 * UNIT - 6 * XSLOT : 14 * UNIT - OFF_GIDX - XSLOT;
  c.co = gemm ? c.so : (wg ? XOFF_CIN1 : XOFF_CIN0) - NF * 128;
  c.co2 = gemm ? XSLOT : CROW;
  c.so2 = c.so + XSLOT + zero;
  c.last = gemm ? slot_of(wg, (nj - 1) | 1) : c.co + ((nj - 1) & ~1) * CROW;
  c.cin = sb + NF * 128 + p * 4;
  const int q = p & 3;
  c.selA = q == 1 ? 0x7610 : 0x5410;
  c.selB = q == 0 ? 0x5432 : 0x7632;
  c.ones = q == 3;
}
template <typename F2, typename F3>
__device__ __forceinline__ void cin_run(CinCtx& c, int nj, uint32_t (&xA)[10][2], float (&accA)[28], uint32_t (&z)[8], F2 before_end, F3 st5) {
  float accB[28];
  uint32_t xB[10][2];
  const uint32_t lastA = nj & 1 ? c.last : 0;
#pragma unroll 1
  for (int j = 0;; j += 2) {
    cin_tail(c, xA, accA, z, 0, c.co != lastA, xB);
    if (c.co == lastA) { before_end(); wg_wait<0>(); cin_finish(c, accA, c.co); break; }
    cin_head(c, xB, accB, z, [&]() { st5(j); cin_finish(c, accA, c.co); });
    cin_tail(c, xB, accB, z, 1, true, xA);
    if (c.co == c.last) { before_end(); wg_wait<0>(); cin_finish(c, accB, c.co + c.co2); break; }
    cin_head(c, xA, accA, z, [&]() { st5(j + 1); cin_finish(c, accB, c.co + c.co2); });
    cin_advance(c);
  }
}

constexpr float ALPHA = 0.3292034911525734f, KAPPA = 2.423681954311584f;
__device__ __forceinline__ float gelu_acc(float v, float ab, float w, float s, float alpha = ALPHA) {
  const float a = fmaf(v, alpha, ab);
  const float u = a * fmaf(a, a, KAPPA);
  float th; asm("tanh.approx.f32 %0, %1;" : "=f"(th) : "f"(u));
  return fmaf(fmaf(a, th, a), w, s);
}

constexpr int QD = 2;
template <int NG>
struct Gelu {
  float4 q[QD + 1];
  uint32_t ep;
  __device__ __forceinline__ void start(uint32_t a) {
    ep = a;
#pragma unroll
    for (int i = 0; i < QD; i++) q[i] = lds128f(ep + i * 64);
  }
  template <int I0, int I1>
  __device__ __forceinline__ void part(float (&d)[4 * NG], float& r0, float& r1, uint32_t done) {
    float alpha;
    asm volatile("{\n.reg .pred p;\nmbarrier.test_wait.parity.shared::cta.b64 p, [%1], 0;\nselp.f32 %0, %2, 0f7FC00000, p;\n}"
                 : "=f"(alpha) : "r"(done), "f"(ALPHA) : "memory");
    part<I0, I1>(d, r0, r1, alpha);
  }
  template <int I0, int I1>
  __device__ __forceinline__ void part(float (&d)[4 * NG], float& r0, float& r1, float alpha = ALPHA) {
#pragma unroll
    for (int i = I0; i < I1; i++) {
      if (i + QD < NG) q[(i + QD) % (QD + 1)] = lds128f(ep + (i + QD) * 64);
      const float4 v = q[i % (QD + 1)];
#pragma unroll
      for (int e = 0; e < 4; e++) asm volatile("" : "+f"(d[4 * i + e]));
      const float al = i < I0 + QD ? alpha : ALPHA;
      r0 = gelu_acc(d[4 * i + 0], v.x, v.z, r0, al);
      r0 = gelu_acc(d[4 * i + 1], v.y, v.w, r0, al);
      r1 = gelu_acc(d[4 * i + 2], v.x, v.z, r1, al);
      r1 = gelu_acc(d[4 * i + 3], v.y, v.w, r1, al);
    }
    asm volatile("" : "+f"(r0), "+f"(r1));
  }
};
__device__ __forceinline__ float quad_sum(float r0, float r1, float r2, float r3, int lane) {
  const bool b0 = lane & 1, b1 = lane & 2;
  const float a = (b0 ? r1 : r0) + __shfl_xor_sync(0xffffffffu, b0 ? r0 : r1, 1);
  const float b = (b0 ? r3 : r2) + __shfl_xor_sync(0xffffffffu, b0 ? r2 : r3, 1);
  return (b1 ? b : a) + __shfl_xor_sync(0xffffffffu, b1 ? a : b, 2);
}
__device__ __forceinline__ void sts128f(uint32_t addr, float a, float b, float c, float d) {
  asm volatile("st.shared.v4.f32 [%0], {%1, %2, %3, %4};" ::"r"(addr), "f"(a), "f"(b), "f"(c), "f"(d) : "memory");
}
__device__ __forceinline__ void pin(float a, float b, uint32_t addr, uint32_t zero) {
  asm volatile("{\n.reg .pred p;\nsetp.ne.u32 p, %3, 0;\n@p st.shared.v2.f32 [%0], {%1, %2};\n}" ::"r"(addr), "f"(a), "f"(b), "r"(zero) : "memory");
}
__device__ __forceinline__ void hand_on(float (&d)[96], const float (&s)[96]) {
#pragma unroll
  for (int i = 0; i < 96; i++) asm volatile("mov.b32 %0, %1;" : "=f"(d[i]) : "f"(s[i]));
}
__device__ __forceinline__ uint64_t desc_x(int u) { return mkdesc(SMEM_BASE, 16, 1024, 1) + u * (UNIT / 16); }
__device__ __forceinline__ uint64_t desc_w(int u, int stride = 1) { return mkdesc(SMEM_BASE, stride * UNIT, 1024, 1) + u * (UNIT / 16); }
__device__ __forceinline__ void tile_step(float (&d)[96], uint64_t dA, uint64_t dB) {
  wg_fence();
#pragma unroll
  for (int k = 0; k < 4; k++) wgmma_ss_n192(d, dA + 2 * k, dB + 128 * k, 1);
  wg_commit();
}
template <int K0 = 0, int K1 = 4>
__device__ __forceinline__ void wide_step(float (&d)[96], float (&e)[32], uint64_t dA, uint64_t dB) {
  wg_fence();
#pragma unroll
  for (int k = K0; k < K1; k++) wgmma_ss_n256(d, e, dA + 2 * k, dB + 128 * k, 1);
  wg_commit();
}
__device__ __forceinline__ int cin_row(int c, int j) {
  if (c >= NGEMM) {
    const int e = (c - NGEMM) * NC_EXTRA + j;
    c = e < 256 ? e >> 1 : NBIG + e - 256;
    j = e < 256 ? 30 + (e & 1) : 29;
  }
  return (c >> 3) * 256 + (c & 2) * 64 + (c & 1) * 64 + (c & 4) * 8 + j;
}
__device__ __forceinline__ int cin_count(int c) {
  return c < NGEMM ? NC_GEMM + (c < NBIG) : NC_EXTRA;
}

__device__ __forceinline__ int fold_i0(int e) { return e < 2 ? 7 * e : 2 + 6 * e; }
__device__ __forceinline__ uint32_t ldg16(const void* p) { uint16_t v; asm volatile("ld.global.nc.u16 %0, [%1];" : "=h"(v) : "l"(p)); return v; }
__device__ __forceinline__ uint4 ldg128(const void* p) {
  uint4 v; asm volatile("ld.global.nc.v4.u32 {%0,%1,%2,%3}, [%4];" : "=r"(v.x), "=r"(v.y), "=r"(v.z), "=r"(v.w) : "l"(p)); return v;
}
__device__ __forceinline__ void sts64f(uint32_t addr, float a, float b) { asm volatile("st.shared.v2.f32 [%0], {%1, %2};" ::"r"(addr), "f"(a), "f"(b) : "memory"); }
__device__ __forceinline__ float to_tf32(float v) { uint32_t r; asm("cvt.rna.tf32.f32 %0, %1;" : "=r"(r) : "f"(v)); return __uint_as_float(r); }
__device__ __forceinline__ uint4 fold_chunk(uint32_t base, const uint4 t0, const uint4 t1) {
  const uint32_t t[8] = {t0.x, t0.y, t0.z, t0.w, t1.x, t1.y, t1.z, t1.w};
  uint32_t v[4];
#pragma unroll
  for (int c = 0; c < 4; c++) {
    const float w0 = __int_as_float(lds32(base + (t[2 * c] & 0xffff))) + __int_as_float(lds32(base + (t[2 * c] >> 16)));
    const float w1 = __int_as_float(lds32(base + (t[2 * c + 1] & 0xffff))) + __int_as_float(lds32(base + (t[2 * c + 1] >> 16)));
    __nv_bfloat162 pk = __floats2bfloat162_rn(w0, w1);
    v[c] = *reinterpret_cast<uint32_t*>(&pk);
  }
  return make_uint4(v[0], v[1], v[2], v[3]);
}
__device__ __forceinline__ int cw_chunk(int u, int n) {
  return ((u < 44 ? (u >> 1) * 1792 : CW_MAIN + ((u - 44) >> 1) * 1024) + (n >> 3) * 256 + (u & 1) * 128 + (n & 7) * 16) >> 4;
}
__device__ __forceinline__ void fold_weights(uint8_t* smem, uint32_t sb, int e, const __nv_bfloat16* __restrict__ wco, const GPtr gp) {
  const int tid = threadIdx.x, lane = tid & 31, warp = tid >> 5;
  const uint32_t bars = sb + OFF_BAR;
  const int i0 = fold_i0(e), i = i0 + warp;
  const bool own = i < fold_i0(e + 1);
  const uint32_t wb16 = ldg16(wco + (lane < NF ? 26 + lane : 0)), wc16 = ldg16(wco + (lane < NF ? 52 + lane : 0));
  const uint32_t w116 = ldg16(wco + (own ? i : 0));
  const uint4* tab = gp.tab;
  const uint4 ta0 = ldg128(tab + 2 * lane), ta1 = ldg128(tab + 2 * lane + 1);
  const uint4 tb0 = ldg128(tab + 64 + 2 * (lane & 15)), tb1 = ldg128(tab + 65 + 2 * (lane & 15));
  asm volatile("barrier.cluster.arrive.relaxed.aligned;\nbarrier.cluster.wait.acquire.aligned;" ::: "memory");
  if (warp >= 6) {
    for (int t = tid - 192; t < 6 * 20; t += 64) sts64f(sb + XOFF_M + 26 * 160 + t * 8, 0.f, 0.f);
    if (warp == 6 && lane < NF) {
      sts64f(sb + XOFF_M + lane * 160 + 104, bf_lo(wb16), 0.f);
      sts64f(sb + XOFF_M + lane * 160 + 112, 0.f, 0.f);
      sts64f(sb + XOFF_M + lane * 160 + 120, 0.f, 0.f);
    }
    if (warp == 7) {
      gp.s->cw[cw_chunk(lane, 28 + e)] = make_uint4(0, 0, 0, 0);
      if (lane < 16) gp.s->cw[cw_chunk(32 + lane, 28 + e)] = make_uint4(0, 0, 0, 0);
    }
  } else {
    mbar_wait(bars + 8 * BAR_GIDX, 0);
    float m0 = 0.f, m1 = 0.f, m2 = 0.f, m3 = 0.f;
    const uint32_t a = sb + XOFF_W3 + (tid < 169 ? tid : 0) * 8;
#pragma unroll 2
    for (int g = 0; g < NF; g++) {
      const int2 v = lds64(a + g * 1352);
      const float w = __shfl_sync(0xffffffffu, bf_lo(wc16), g);
      m0 = fmaf(w, bf_lo(v.x), m0); m1 = fmaf(w, bf_hi(v.x), m1);
      m2 = fmaf(w, bf_lo(v.y), m2); m3 = fmaf(w, bf_hi(v.y), m3);
    }
    if (tid < 169) {
      const int o = tid * 2, o2 = o + 1;
      sts64f(sb + XOFF_M + (o / 13) * 160 + (o % 13) * 8, to_tf32(m0), to_tf32(m1));
      sts64f(sb + XOFF_M + (o2 / 13) * 160 + (o2 % 13) * 8, to_tf32(m2), to_tf32(m3));
    }
  }
  const uint32_t sT = sb + XOFF_S + warp * 2 * 3136, sA = sT + 3136;
  const int g = lane >> 2, c = lane & 3;
  uint32_t af[2][8];
  mbar_wait(bars + 8 * BAR_FULL, 0);
  if (own) {
#pragma unroll
    for (int k = 0; k < 8; k++) {
      const int h = 4 * k + c;
      const uint32_t a = sb + XOFF_W2 + ((h < NF ? h : 0) * 676 + i * 26 + 2 * g) * 2;
      af[0][k] = lds32(a);
      af[1][k] = lds32(a + (g < 5 ? 32 : 0));
    }
#pragma unroll 1
    for (int o = lane; o < 338; o += 32) {
      const uint32_t v = lds32(sb + XOFF_W1 + (i - (i0 & ~1)) * 1352 + o * 4);
      sts64f(sA + (o / 13) * 112 + (o % 13) * 8, bf_lo(v), bf_hi(v));
    }
    if (lane < 28) sts64f(sA + lane * 112 + 104, 0.f, 0.f);
    if (lane < 2) sts64f(sT + (26 + lane) * 112 + 104, lane == 0 ? bf_lo(w116) : 0.f, 0.f);
  }
  bar_sync<4, 256>();
  if (own) {
#pragma unroll 1
    for (int n = 0; n < 4; n++) {
      float d[2][4] = {};
#pragma unroll
      for (int ks = 0; ks < 4; ks++) {
        const uint32_t b0 = lds32(sb + XOFF_M + (8 * ks + c) * 160 + (8 * n + g) * 4);
        const uint32_t b1 = lds32(sb + XOFF_M + (8 * ks + c + 4) * 160 + (8 * n + g) * 4);
#pragma unroll
        for (int m = 0; m < 2; m++)
          asm volatile("mma.sync.aligned.m16n8k8.row.col.f32.tf32.tf32.f32 {%0,%1,%2,%3}, {%4,%5,%6,%7}, {%8,%9}, {%0,%1,%2,%3};"
                       : "+f"(d[m][0]), "+f"(d[m][1]), "+f"(d[m][2]), "+f"(d[m][3])
                       : "r"(af[m][2 * ks] << 16), "r"(af[m][2 * ks] & 0xffff0000u), "r"(af[m][2 * ks + 1] << 16),
                         "r"(af[m][2 * ks + 1] & 0xffff0000u), "r"(b0), "r"(b1));
      }
      if (n < 3 || c < 2) {
        const uint32_t a = sT + 2 * g * 112 + (8 * n + 2 * c) * 4;
        sts64f(a, d[0][0], d[0][1]);
        sts64f(a + 112, d[0][2], d[0][3]);
        if (g < 5) {
          sts64f(a + 16 * 112, d[1][0], d[1][1]);
          sts64f(a + 17 * 112, d[1][2], d[1][3]);
        }
      }
    }
    __syncwarp();
    const int nt = i < 24 ? i : 2 * i - 24, na = i < 24 ? 32 + i : 2 * i - 23;
#pragma unroll 1
    for (int k = 0; k < 3; k++) {
      const bool isa = k == 1 || (k == 2 && lane >= 16);
      const uint4 v = fold_chunk(isa ? sA : sT, k < 2 ? ta0 : tb0, k < 2 ? ta1 : tb1);
      if (k < 2 || lane < 28 || na < 32) gp.s->cw[cw_chunk(k < 2 ? lane : 32 + (lane & 15), isa ? na : nt)] = v;
    }
  }
  __syncwarp();
  if (lane == 0) flag_add(&gp.s->foldflag);
  bar_sync<4, 256>();
  mbar_wait(bars + 8 * BAR_GDONE, 0);
  if (tid >= 128 && tid < 132) mbar_arrive(ev_bar(bars, EV_END));
}

__global__ void __cluster_dims__(2, 1, 1) __launch_bounds__(384, 1)
xdeepfm_kernel(const int* __restrict__ idx, const __nv_bfloat16* __restrict__ table, const __nv_bfloat16* __restrict__ w1,
               const __nv_bfloat16* __restrict__ b1, const __nv_bfloat16* __restrict__ w2,
               const __nv_bfloat16* __restrict__ ws, const __nv_bfloat16* __restrict__ wco,
               const __nv_bfloat16* __restrict__ bout, __nv_bfloat16* __restrict__ out, const GPtr gp,
               const __grid_constant__ CUtensorMap tmW, const __grid_constant__ CUtensorMap tmT,
               const __grid_constant__ CUtensorMap tmS, const __grid_constant__ CUtensorMap tmC) {
  int myidx, idx1, idx2 = 0, idx3 = 0;
  {
    const int t = threadIdx.x, b = blockIdx.x, half = (b >> 1) ^ (t >= 256 ? t >> 4 : 0);
    const int* ip = idx + (((b >> 3) & 15) * 256 + (half & 1) * 128 + (t < 256 ? t >> 1 : (b & 1) * 64 + ((t >> 1) & 48) + (t & 15))) * NF;
    asm volatile("{\n.reg .pred p;\nsetp.ge.u32 p, %5, 256;\nld.global.nc.v2.s32 {%0, %1}, [%4];\n@p ld.global.nc.v2.s32 {%2, %3}, [%4 + 8];\n}"
                 : "=r"(myidx), "=r"(idx1), "+r"(idx2), "+r"(idx3) : "l"(ip), "r"(t));
  }
  extern __shared__ __align__(1024) uint8_t smem[];
  const uint32_t sb = (uint32_t)__cvta_generic_to_shared(smem);
  const uint32_t bars = sb + OFF_BAR;
  const int tid = threadIdx.x, lane = tid & 31;
  const int warp = __shfl_sync(0xffffffffu, tid >> 5, 0);
  const int cta = blockIdx.x;
  const bool gemm = cta < NGEMM;
  const int nt = cta & 7, rank = cta & 1;

  if (warp == 8 && elect1()) {
    mbar_init(bars + 8 * BAR_GIDX, 1);
    mbar_init(bars + 8 * BAR_FULL, 1);
    mbar_init(bars + 8 * BAR_W0, 1);
    asm volatile("fence.mbarrier_init.release.cluster;" ::: "memory");
    if (gemm) {
      mbar_expect_tx(bars + 8 * BAR_W0, 4 * UNIT);
#pragma unroll
      for (int i = 0; i < 4; i++)
        tma_load(sb + (U_W + i) * UNIT, &tmW, i < 3 ? nt * 192 + i * 64 : 1536 + (nt >> 2) * 64, 0, bars + 8 * BAR_W0);
    } else {
      mbar_expect_tx(bars + 8 * BAR_GIDX, 35152);
      bulk_load(sb + XOFF_W3, ws + 2 * 17576, 35152, bars + 8 * BAR_GIDX);
    }
  }
  if (threadIdx.x < 256) {}
  else if (threadIdx.x >= 384 - 16) {
    const int l = threadIdx.x & 7;
    if (l < 7) asm volatile("prefetch.global.L2 [%0];" ::"l"(w1 + (((cta >> 3 & 15) * 2 + (cta & 1)) * 2 + ((threadIdx.x >> 3) & 1)) * DIN + (l < 6 ? (cta & 6) * 192 + l * 64 : 1536 + (cta & 4) * 16)));
  }
  else if (threadIdx.x >= 352 && threadIdx.x < 359) {
    const int l = blockIdx.x * 7 + threadIdx.x - 352;
    if (l < 824) asm volatile("prefetch.global.L2 [%0];" ::"l"(ws + (823 - l) * 64));
  }

  if (warp >= 8) {
    const int pw = warp - 8;
    const bool lead = elect1();
    if (lead) {
      if (pw) mbar_init(bars + 8 * (pw < 3 ? BAR_FULL + pw : BAR_X0), 1);
      else mbar_init(bars + 8 * BAR_GDONE, 4);
      asm volatile("fence.mbarrier_init.release.cluster;" ::: "memory");
    }
    __syncwarp();
    asm volatile("barrier.cluster.arrive.relaxed.aligned;" ::: "memory");
    if (lead) {
      if (gemm) w_prefetch(w1, 1, cta, pw);
      if (pw == 0) {
        if (gemm) {
          mbar_expect_tx(bars + 8 * BAR_FULL, 2 * UNIT);
          asm volatile("prefetch.tensormap [%0];" ::"l"(&tmT) : "memory");
          asm volatile("prefetch.tensormap [%0];" ::"l"(&tmS) : "memory");
        } else {
          const int i0 = fold_i0(cta - NGEMM) & ~1, ni = NF - i0 < 8 ? NF - i0 : 8;
          mbar_expect_tx(bars + 8 * BAR_FULL, 35152 + ni * 1352);
          bulk_load(sb + XOFF_W1, ws + i0 * 676, ni * 1352, bars + 8 * BAR_FULL);
          bulk_load(sb + XOFF_W2, ws + 17576, 35152, bars + 8 * BAR_FULL);
        }
      }
    }
    __syncwarp();
    asm volatile("setmaxnreg.dec.sync.aligned.u32 24;");
    if (elect1()) {
      mbar_init(bars + 8 * (BAR_EV + pw), 4);
      mbar_init(bars + 8 * (BAR_EV + 4 + pw), 4);
      mbar_init(bars + 8 * (BAR_FULL + 4 + pw), 1);
      if (pw < 3) mbar_init(bars + 8 * (pw == 2 ? BAR_CW : BAR_DNN + pw), pw == 0 && !gemm ? 4 : 1 + (pw & 1));
      if (pw < 2) mbar_init(bars + 8 * (pw ? BAR_PARK : BAR_FULL + 3), 1 + 7 * pw);
#pragma unroll
      for (int i = 0; i < 4; i++) mbar_init(bars + 8 * (BAR_CFULL + pw * 4 + i), 1);
      if (pw < 2) mbar_init(bars + 8 * (BAR_C0 + pw), 1);
      asm volatile("fence.mbarrier_init.release.cluster;" ::: "memory");
    }
    __syncwarp();
    bar_sync<6, 128>();
    asm volatile("barrier.cluster.wait.acquire.aligned;" ::: "memory");
    if (gemm) {
      {
        const uint32_t a = sb + OFF_GIDX + ((lane >> 4) * 64 + pw * 16 + (lane & 15)) * NF * 4;
        asm volatile("st.shared.v2.b32 [%0], {%1, %2};\nst.shared.v2.b32 [%0 + 8], {%3, %4};"
                     ::"r"(a), "r"(myidx), "r"(idx1), "r"(idx2), "r"(idx3) : "memory");
        __syncwarp();
      }
      if (elect1()) {
#pragma unroll
        for (int j = 0; j < 16; j += 8) {
          int r[8];
#pragma unroll
          for (int i = 0; i < 8; i++) r[i] = lds32(sb + OFF_GIDX + ((64 + pw * 16 + j + i) * NF) * 4);
#pragma unroll
          for (int i = 0; i < 8; i++) tma_row_mc(sb + U_XB * UNIT + (rank * 64 + pw * 16 + j + i) * 128, &tmT, r[i], bars + 8 * BAR_FULL);
        }
        int s = 1;
#pragma unroll 1
        for (int fi = 1; fi < NF; fi++) {
          const int f = fresh(fi), pw = fresh(warp) - 8, ct = fresh(cta), nt = ct & 7;
          const int t = f - FS, st = t < 0 ? s : (t & 3) ^ ((t >> 1) & 1), e = f - 3 - (t > 1);
          const uint32_t fb = bars + 8 * (BAR_FULL + (f & 7)), ia = sb + OFF_GIDX + (pw * 16 * NF + f) * 4;
          const uint32_t d = sb + (st == 3 ? U_SP : 2 * st) * UNIT + ((ct & 1) * 64 + pw * 16) * 128;
          if (f == 4) mbar_wait(bars + 8 * BAR_GIDX, 0);
          int r[2][RB];
#pragma unroll
          for (int i = 0; i < RB; i++) r[0][i] = lds32(ia + i * NF * 4);
          if (e >= 0) mbar_wait(ev_bar(bars, e), ev_par(e));
          if (pw == 0) mbar_expect_tx(fb, t < 0 ? 8 * UNIT : 6 * UNIT);
#pragma unroll
          for (int j = 0; j < 16 / RB; j++) {
#pragma unroll
            for (int i = 0; i < RB; i++) r[(j + 1) & 1][i] = lds32(ia + (RB * j + RB + i + (RB * j + RB >= 16) * 48) * NF * 4);
#pragma unroll
            for (int i = 0; i < RB; i++) tma_row_mc(d + (RB * j + i) * 128, &tmT, r[j & 1][i], fb);
          }
          if (t < 0) {
#pragma unroll
            for (int j = 0; j < 16 / RB; j++) {
              if (j + 1 < 16 / RB) {
#pragma unroll
                for (int i = 0; i < RB; i++) r[(j + 1) & 1][i] = lds32(ia + (64 + RB * j + RB + i) * NF * 4);
              }
#pragma unroll
              for (int i = 0; i < RB; i++) tma_row_mc(d + U_XB * UNIT + (RB * j + i) * 128, &tmT, r[j & 1][i], fb);
            }
          }
          tma_load(sb + (U_W + 4 * st + pw) * UNIT, &tmW, pw < 3 ? nt * 192 + pw * 64 : 1536 + (nt >> 2) * 64, f * 64, fb);
          if (f == GI && pw < 2) {
            if (pw == 0) mbar_expect_tx(bars + 8 * BAR_GIDX, 128 * NF * 4);
            bulk_load(sb + OFF_GIDX + pw * 64 * NF * 4, idx + ((ct >> 3) * 256 + (((ct >> 1) ^ pw) & 1) * 128 + (ct & 1) * 64) * NF, 64 * NF * 4, bars + 8 * BAR_GIDX);
          }
          if (f == GI && pw == 2) asm volatile("prefetch.tensormap [%0];" ::"l"(&tmC) : "memory");
          if (f + WD < NF) w_prefetch(w1, f + WD, ct, pw);
          if (++s == 3) s = 0;
        }
        mbar_wait(bars + 8 * BAR_T, 0);
#pragma unroll 1
        for (int ti = 0; ti < 8; ti++) {
          const int t = fresh(ti), pw = fresh(warp) - 8, e = t < 4 ? 22 - !t : 19 + t;
          const uint32_t ia = sb + OFF_TIDX + t * 256 + pw * 64, fb = bars + 8 * (BAR_FULL + ((NF + t) & 7));
          const uint32_t d = sb + b_x(t) * UNIT + ((fresh(cta) & 1) * 64 + pw * 16) * 128;
          int4 r[2];
          r[0] = lds128(ia);
          r[1] = lds128(ia + 16);
          mbar_wait(ev_bar(bars, e), ev_par(e));
          if (pw == 0) mbar_expect_tx(fb, t < 3 ? 2 * UNIT : 5 * UNIT);
#pragma unroll
          for (int j = 0; j < 4; j++) {
            tma_row_mc(d + (4 * j + 0) * 128, &tmT, r[j & 1].x, fb);
            tma_row_mc(d + (4 * j + 1) * 128, &tmT, r[j & 1].y, fb);
            tma_row_mc(d + (4 * j + 2) * 128, &tmT, r[j & 1].z, fb);
            tma_row_mc(d + (4 * j + 3) * 128, &tmT, r[j & 1].w, fb);
            if (j < 2) r[j & 1] = lds128(ia + 32 + 16 * j);
          }
        }
        mbar_arrive(bars + 8 * BAR_GDONE);
      }
      __syncwarp();
    }
    asm volatile("setmaxnreg.inc.sync.aligned.u32 %0;" ::"n"(PREG));
    {
    int cta; asm volatile("mov.u32 %0, %%ctaid.x;" : "=r"(cta));
    int tid; asm volatile("mov.u32 %0, %%tid.x;" : "=r"(tid));
    const int lane = tid & 31, pw = __shfl_sync(0xffffffffu, tid >> 5, 0) - 8;
    const bool gemm = cta < NGEMM;
    const int bt = cta >> 3, nt = cta & 7;
    const int ncin = cin_count(cta);
    unsigned epoch;
    auto load_cw = [&]() {
      if (elect1()) {
        asm volatile("fence.proxy.async.global;" ::: "memory");
        mbar_expect_tx(bars + 8 * BAR_CW, CW_BYTES);
        bulk_load(sb + OFF_CW, gp.s->cw, CW_CUT * 1792, bars + 8 * BAR_CW);
        bulk_load(sb + OFF_CW2, gp.s->cw + CW_CUT * 1792 / 16, (22 - CW_CUT) * 1792, bars + 8 * BAR_CW);
        bulk_load(sb + OFF_CWL, gp.s->cw + CW_MAIN / 16, CW_LIN, bars + 8 * BAR_CW);
      }
    };
    if (!gemm) {
      epoch = gp.s->epoch[cta] + 1;
#pragma unroll 1
      for (int i = pw * 32 + lane; i < NC_EXTRA * 13; i += 128)
        asm volatile("cp.async.ca.shared.global [%0], [%1], 8;" ::"r"(sb + XOFF_CIDX + i * 8), "l"(idx + cin_row(cta, i / 13) * NF + i % 13 * 2) : "memory");
      if (elect1()) {
#pragma unroll 1
        for (int i = 0; i < NPAIR; i++) mbar_init(sb + XOFF_BAR + (pw * NPAIR + i) * 8, pw & 1 ? 4 : 1);
        asm volatile("fence.mbarrier_init.release.cluster;" ::: "memory");
      }
      asm volatile("cp.async.wait_all;" ::: "memory");
      bar_sync<6, 128>();
      if (elect1()) mbar_arrive(bars + 8 * BAR_GDONE);
      __syncwarp();
      if (pw == 3) {
        flag_wait(&gp.s->foldflag, epoch * NEXTRA * 8, 0);
        __syncwarp();
        load_cw();
      }
      if (elect1()) {
        const int wg = pw & 1;
#pragma unroll 1
        for (int t = pw < 2 ? -1 : 1; t < NPAIR; t += t < 0 ? 1 : 2) {
          const int j = t < 0 ? 0 : 2 * t + 1, n = t < 0 || t == NPAIR - 1 ? 1 : 2;
          const uint32_t cb = t < 0 ? bars + 8 * (BAR_C0 + wg) : sb + XOFF_BAR + (wg * 2 * NPAIR + t) * 8;
          if (t == 0 || t == 1) mbar_wait(ev_bar(bars, EV_END), ev_par(EV_END));
          if (t >= 4) mbar_wait(cb + 8 * (NPAIR - 4), 0);
          mbar_expect_tx(cb, n * NF * 128);
#pragma unroll 1
          for (int i = 0; i < n; i++) {
            const uint32_t d = sb + (t < 0 ? OFF_GIDX + wg * XSLOT : XOFF_SLOT + (wg * 8 + (t & 3) * 2 + i) * XSLOT);
            const uint32_t ia = sb + XOFF_CIDX + (wg * (NC_EXTRA / 2) + j + i) * NF * 4;
#pragma unroll
            for (int k = 0; k < NF; k += 2) {
              const int2 r = lds64(ia + k * 4);
              tma_row(d + k * 128, &tmT, r.x, cb);
              tma_row(d + (k + 1) * 128, &tmT, r.y, cb);
            }
          }
        }
      }
      __syncwarp();
    } else {
      epoch = lds32(bars + 8 * BAR_EPOCH);
      if (pw == 3) {
        mbar_wait(ev_bar(bars, EV_CW), ev_par(EV_CW));
        load_cw();
      }
      constexpr int n0 = NC_WG0;
      const uint32_t ep = sb + OFF_EPI + (lane & 3) * 16, pk = sb + (pw * 32 + lane) * 16;
      float r2 = 0.f, r3 = 0.f;
      mbar_wait(bars + 8 * BAR_GDONE, 0);
      mbar_wait(bars + 8 * BAR_X0, 0);
      asm volatile("fence.proxy.async.global;" ::: "memory");
#pragma unroll 1
      for (int k = 0; k < 5; k++) {
        const int n = pw + 4 * k, wg = n > 1 && ((n & 1) || n == 2), j = n == 1 ? 1 : n < 3 ? 0 : n - 1 - wg;
        const int m = min((wg ? ncin - n0 : n0) - j, j ? 2 : 1), r = wg * n0 + j;
        const uint32_t cb = bars + 8 * (j ? BAR_CFULL + wg * 8 + (j >> 1) : BAR_C0 + wg), d = sb + slot_of(wg, j);
        if (n >= 2 && n < 12) {
          const int e = n == 2 ? EV_CW : n < 7 ? EV_SLOT : EV_END;
          mbar_wait(ev_bar(bars, e), ev_par(e));
        }
        auto load_sample = [&](int i) {
          const int4 u = lds128(sb + OFF_CIDX + (r + i) * 32), v = lds128(sb + OFF_CIDX + (r + i) * 32 + 16);
          const uint32_t a = d + i * XSLOT;
          tma_row(a, &tmC, (cta * 32 + r + i) * FS, cb);
          tma_row(a + (FS + 0) * 128, &tmT, u.x, cb);
          tma_row(a + (FS + 1) * 128, &tmT, u.y, cb);
          tma_row(a + (FS + 2) * 128, &tmT, u.z, cb);
          tma_row(a + (FS + 3) * 128, &tmT, u.w, cb);
          tma_row(a + (FS + 4) * 128, &tmT, v.x, cb);
          tma_row(a + (FS + 5) * 128, &tmT, v.y, cb);
          tma_row(a + (FS + 6) * 128, &tmT, v.z, cb);
          tma_row(a + (FS + 7) * 128, &tmT, v.w, cb);
        };
        if (m > 0 && elect1()) {
          mbar_expect_tx(cb, m * NF * 128);
          load_sample(0);
          if (m > 1) load_sample(1);
        }
        __syncwarp();
        if (k == 0 || k == 4) continue;
        if (k == 1) {
          mbar_wait(bars + 8 * BAR_PARK, 0);
        }
        uint32_t a = k == 3 ? OFF_PARK2 : OFF_PARK + (k - 1) * 8 * 2048, b = (k - 1) * 8 * 64;
#pragma unroll 1
        for (const uint32_t e = b + 8 * 64; b != e; a += BGN * 2048, b += BGN * 64) {
          float4 v[BGN], q[BGN];
#pragma unroll
          for (int i = 0; i < BGN; i++) { v[i] = lds128f(pk, a + i * 2048); q[i] = lds128f(ep, b + i * 64); }
#pragma unroll
          for (int i = 0; i < BGN; i++) {
            r2 = gelu_acc(v[i].x, q[i].x, q[i].z, r2);
            r3 = gelu_acc(v[i].z, q[i].x, q[i].z, r3);
            r2 = gelu_acc(v[i].y, q[i].y, q[i].w, r2);
            r3 = gelu_acc(v[i].w, q[i].y, q[i].w, r3);
          }
        }
      }
      const float4 w = lds128f(pk + OFF_RS0);
      const int2 v = lds64(sb + OFF_RS1 + (pw * 32 + lane) * 8);
      uint2* dst = gp.s->part + (nt * NB + bt * 256 + pw * 16);
      const uint32_t o = (lane & 1) * 8 + (lane & 2) * 32 + (lane >> 2);
      put_tagged(dst + (o ^ ((cta & 2) * 64 + (~cta & 1) * 64)), quad_sum(w.x, w.y, w.z, w.w, lane), epoch);
      put_tagged(dst + (o ^ ((~cta & 2) * 64)), quad_sum(__int_as_float(v.x), __int_as_float(v.y), r2, r3, lane), epoch);
    }
    if (pw == 3 || !gemm) {
      float s = (sb & 0xFFFFFF) == SMEM_BASE ? bf2f(bout[0]) : __int_as_float(0x7fc00000);
      const int r = gemm ? lane : pw * (NC_EXTRA / 4) + min(lane, NC_EXTRA / 4 - 1), row = cin_row(cta, r);
      const uint2* src = gp.s->part + row;
      uint2 v[8];
#pragma unroll 1
      for (int i = 0; i < 100000; i++) {
        unsigned miss = 0;
#pragma unroll
        for (int n = 0; n < 8; n++)
          asm volatile("ld.relaxed.gpu.global.v2.b32 {%0, %1}, [%2];" : "=r"(v[n].x), "=r"(v[n].y) : "l"(src + n * NB) : "memory");
#pragma unroll
        for (int n = 0; n < 8; n++) miss |= v[n].y ^ epoch;
        if (__all_sync(0xffffffffu, miss == 0)) break;
        __nanosleep(POLL);
      }
#pragma unroll
      for (int n = 0; n < 8; n++) s += __uint_as_float(v[n].x);
      sts64f(sb + OFF_DNN + r * 8, s, __int_as_float(row));
      __syncwarp();
      if (lane == 0) mbar_arrive(bars + 8 * BAR_DNN);
      if (pw == 3 && lane == 0) gp.s->epoch[fresh(cta)] = epoch;
    }
    }
  } else {
    const int wg = warp >> 2;
    const int p = tid & 127;
    if (gemm) {
      asm volatile("barrier.cluster.arrive.relaxed.aligned;" ::: "memory");
#pragma unroll
      for (int i = 0; i < 4; i++) {
        const int r = __shfl_sync(0xffffffffu, myidx, 8 * i + 2 * (lane >> 3));
        const int row = warp * 16 + 4 * i + (lane >> 3);
        cpasync16(sb + row * 128 + (((lane & 7) ^ (row & 7)) << 4), table + (size_t)r * 64 + (lane & 7) * 8);
      }
      asm volatile("barrier.cluster.wait.acquire.aligned;" ::: "memory");
    } else {
      fold_weights(smem, sb, cta - NGEMM, wco, gp);
    }
    asm volatile("setmaxnreg.inc.sync.aligned.u32 224;");
    float r0 = 0.f, r1 = 0.f, r2 = 0.f, r3 = 0.f;
    CinCtx c;
    float accA[28];
    uint32_t xA[10][2], z[8];
    const uint32_t ep = sb + OFF_EPI + (lane & 3) * 16;
    auto load_w = [&](int t) {
      const int w = warp & 3;
      if (w < 3 && elect1())
        tma_load(sb + (b_w(t) + b_ws(t) * w) * UNIT, &tmW, nt * 192 + w * 64, (NF - 1 - t) * 64, bars + 8 * (BAR_FULL + ((NF + t) & 7)));
    };
    auto keep_x = [&](int f, int u) {
      if (warp == 0 && elect1()) tma_store(&tmS, f * 64, cta * 32, sb + (u + rank) * UNIT + (nt >> 2) * 4096);
    };
    auto role = [&](int w) { int c; asm volatile("mov.u32 %0, %%ctaid.x;" : "=r"(c)); return c < NGEMM && wg == w; };
    if (role(0)) {
      asm volatile("setmaxnreg.inc.sync.aligned.u32 256;");
      float d0[96], dx[32], dw[96];
      Gelu<24> g0;
      mbar_wait(bars + 8 * BAR_W0, 0);
      asm volatile("cp.async.wait_all;" ::: "memory");
      asm volatile("fence.proxy.async.shared::cta;" ::: "memory");
      bar_sync<2, 256>();
      const uint64_t dA0 = desc_x(rank), dA1 = desc_x(rank ^ 1);
      wg_fence();
#pragma unroll
      for (int k = 0; k < 4; k++) {
        wgmma_ss_n256(dw, dx, dA0 + 2 * k, desc_w(U_W) + 128 * k, k != 0);
        wgmma_ss_n192(d0, dA1 + 2 * k, desc_w(U_W) + 128 * k, k != 0);
      }
      wg_commit();
      keep_x(0, 0);
#pragma unroll 1
      for (int f = 1; f < NF - 3; f++) {
        mbar_wait(bars + 8 * (BAR_FULL + (f & 7)), (f >> 3) & 1);
        const int st = (STAGES >> (2 * f)) & 3, xo = (st == 3 ? U_SP : 2 * st) * (UNIT / 16);
        const uint64_t dB = desc_w(U_W + 4 * st);
        wg_fence();
        wgmma_ss_n256(dw, dx, dA0 + xo, dB, 1);
        wgmma_ss_n192(d0, dA1 + xo, dB, 1);
        wg_commit();
        store_read<0>();
        wg_wait<1>();
        if (p < (f > FS ? 4 : 2)) mbar_arrive_cta(ev_bar(bars, f - 1), p & 1);
#pragma unroll
        for (int k = 1; k < 4; k++) {
          wgmma_ss_n256(dw, dx, dA0 + xo + 2 * k, dB + 128 * k, 1);
          wgmma_ss_n192(d0, dA1 + xo + 2 * k, dB + 128 * k, 1);
        }
        wg_commit();
        if (f < FS) keep_x(f, 2 * st);
      }
      {
        constexpr int x3 = 2 * (UNIT / 16), x4 = U_SP * (UNIT / 16), x5 = 4 * (UNIT / 16);
        const uint64_t dB3 = desc_w(U_W + 4), dB4 = desc_w(U_W + 12), dB5 = desc_w(U_W + 8);
        mbar_wait(bars + 8 * (BAR_FULL + 7), 0);
        tile_step(d0, dA1 + x3, dB3);
        wg_wait<1>();
        if (p < 4) mbar_arrive_cta(ev_bar(bars, NF - 4), p & 1);
        mbar_wait(bars + 8 * (BAR_FULL + 0), 1);
        tile_step(d0, dA1 + x4, dB4);
        mbar_wait(bars + 8 * (BAR_FULL + 1), 1);
        tile_step(d0, dA1 + x5, dB5);
        wide_step(dw, dx, dA0 + x3, dB3);
        g0.start(ep);
        wg_wait<1>();
        wide_step(dw, dx, dA0 + x4, dB4);
        g0.part<0, PE1>(d0, r0, r1, bars + 8 * BAR_W0);
        pin(r0, r1, ep, gp.zero);
        wg_wait<1>();
        if (p < 4) mbar_arrive_cta(ev_bar(bars, NF - 3), p & 1);
        wide_step<0, HK>(dw, dx, dA0 + x5, dB5);
        g0.part<PE1, PE2>(d0, r0, r1, bars + 8 * BAR_W0);
        pin(r0, r1, ep, gp.zero);
        wg_wait<1>();
        bar_arrive<4, 256>();
        if (p < 4) mbar_arrive_cta(ev_bar(bars, NF - 2), p & 1);
        wide_step<HK, 4>(dw, dx, dA0 + x5, dB5);
        g0.part<PE2, PE0>(d0, r0, r1);
        pin(r0, r1, ep, gp.zero);
        wg_wait<0>();
        load_w(3);
        if (p < 4) mbar_arrive_cta(ev_bar(bars, NF - 1), p & 1);
        asm volatile("cp.async.bulk.wait_group 0;" ::: "memory");
        if (warp == 0 && elect1()) mbar_arrive(bars + 8 * BAR_X0);
      }
      g0.part<PE0, 24>(d0, r0, r1);
      Gelu<8> gx;
      gx.start(ep + 24 * 64);
      gx.part<0, 8>(dx, r2, r3);
      float d1[96];
      hand_on(d1, dw);
      asm volatile("setmaxnreg.dec.sync.aligned.u32 224;");
      Gelu<24> g1;
      g1.start(ep);
      g1.part<0, 24>(d1, r2, r3);
    }
    if (role(1)) {
      float d0[96], dw[96];
      asm volatile("cp.async.wait_all;" ::: "memory");
      asm volatile("fence.proxy.async.shared::cta;" ::: "memory");
      bar_arrive<2, 256>();
      {
        const int col = p < 96 ? nt * 96 + p : 768 + (nt >> 2) * 32 + (p - 96);
        const uint32_t bb = __ldg(reinterpret_cast<const uint32_t*>(b1) + col), ww = __ldg(reinterpret_cast<const uint32_t*>(w2) + col);
        reinterpret_cast<float4*>(smem + OFF_EPI)[p] =
            make_float4(ALPHA * bf_lo(bb), ALPHA * bf_hi(bb), (0.5f / ALPHA) * bf_lo(ww), (0.5f / ALPHA) * bf_hi(ww));
      }
      mbar_wait(bars + 8 * BAR_W0, 0);
      mbar_wait(bars + 8 * BAR_FULL, 0);
      wg_fence();
#pragma unroll
      for (int k = 0; k < 4; k++) {
        wgmma_ss_n192(d0, desc_x(U_XB) + 2 * k, desc_w(U_W) + 128 * k, k != 0);
        wgmma_ss_n192(dw, desc_x(U_XB + 1) + 2 * k, desc_w(U_W) + 128 * k, k != 0);
      }
      wg_commit();
      int s = 1;
#pragma unroll 1
      for (int f = 1; f < FS; f++) {
        mbar_wait(bars + 8 * (BAR_FULL + (f & 7)), (f >> 3) & 1);
        const uint64_t dA = desc_x(U_XB + 2 * s), dB = desc_w(U_W + 4 * s);
        wg_fence();
        wgmma_ss_n192(d0, dA, dB, 1);
        wgmma_ss_n192(dw, dA + 512, dB, 1);
        wg_commit();
        wg_wait<1>();
        if (p < 2) mbar_arrive_cta(ev_bar(bars, f - 1), p);
#pragma unroll
        for (int k = 1; k < 4; k++) {
          wgmma_ss_n192(d0, dA + 2 * k, dB + 128 * k, 1);
          wgmma_ss_n192(dw, dA + 512 + 2 * k, dB + 128 * k, 1);
        }
        wg_commit();
        if (++s == 3) s = 0;
      }
      wg_wait<0>();
      if (p < 2) mbar_arrive_cta(ev_bar(bars, FS - 1), p);
      {
        const uint32_t a = sb + OFF_GIDX + 64 * NF * 4;
        int v[4];
#pragma unroll
        for (int i = 0; i < 4; i++) v[i] = lds32(a + (((p & 15) * 4 + i) * NF + (NF - 1 - (p >> 4))) * 4);
        const int2 w = lds64(sb + OFF_GIDX + (((nt >> 2) * 32 + (p >> 2)) * NF + FS + (p & 3) * 2) * 4);
        asm volatile("st.shared.v2.b32 [%0], {%1, %2};" ::"r"(sb + OFF_CIDX + p * 8), "r"(w.x), "r"(w.y) : "memory");
        bar_sync<3, 128>();
        asm volatile("st.shared.v4.b32 [%0], {%1, %2, %3, %4};" ::"r"(sb + OFF_TIDX + p * 16), "r"(v[0]), "r"(v[1]), "r"(v[2]), "r"(v[3]) : "memory");
        bar_sync<3, 128>();
        if (p < 2) {
          const unsigned epoch = gp.s->epoch[cta] + 1;
          flag_wait(&gp.s->foldflag, epoch * NEXTRA * 8, 0);
          sts32f(bars + 8 * BAR_EPOCH, __uint_as_float(epoch));
          mbar_arrive(bars + 8 * BAR_T);
        }
        __syncwarp();
      }
      mbar_wait(ev_bar(bars, FS), ev_par(FS));
      mbar_wait(bars + 8 * (BAR_FULL + 2), 1);
      bar_sync<4, 256>();
#pragma unroll
      for (int t = 0; t < 4; t++) {
        if (t) mbar_wait(bars + 8 * (BAR_FULL + 2 + t), 1);
        const uint64_t dA = desc_x(b_x(t)), dB = desc_w(b_w(t), b_ws(t));
        wg_fence();
#pragma unroll
        for (int k = 0; k < 4; k++) {
          wgmma_ss_n192(d0, dA + 2 * k, dB + 128 * k, 1);
          wgmma_ss_n192(dw, dA + 512 + 2 * k, dB + 128 * k, 1);
          if (k == 1 && t) {
            wg_commit();
            wg_wait<1>();
            wg_fence();
          }
        }
        wg_commit();
        if (t) {
          if (t == 1) mbar_wait(ev_bar(bars, NF - 1), ev_par(NF - 1));
          load_w(3 + t);
          if (t == 1 && p < 4) mbar_arrive_cta(ev_bar(bars, 26), p & 1);
        }
      }
      mbar_wait(bars + 8 * (BAR_FULL + 6), 1);
      tile_step(d0, desc_x(b_x(4)), desc_w(b_w(4)));
      wg_wait<1>();
      load_w(7);
      if (p < 4) mbar_arrive(ev_bar(bars, EV_CW));
      mbar_wait(bars + 8 * (BAR_FULL + 7), 1);
      tile_step(d0, desc_x(b_x(5)), desc_w(b_w(5)));
      mbar_wait(bars + 8 * (BAR_FULL + 0), 0);
      tile_step(d0, desc_x(b_x(6)), desc_w(b_w(6)));
      mbar_wait(bars + 8 * (BAR_FULL + 1), 0);
      tile_step(d0, desc_x(b_x(7)), desc_w(b_w(7), 4));
      tile_step(dw, desc_x(b_x(4) + 1), desc_w(b_w(4)));
      Gelu<24> g0;
      g0.start(ep);
      wg_wait<1>();
      tile_step(dw, desc_x(b_x(5) + 1), desc_w(b_w(5)));
      g0.part<0, PS>(d0, r0, r1);
      pin(r0, r1, ep, gp.zero);
      wg_wait<1>();
      if (p < 4) mbar_arrive(ev_bar(bars, 30));
      tile_step(dw, desc_x(b_x(6) + 1), desc_w(b_w(6)));
      g0.part<PS, PS + PS2>(d0, r0, r1);
      pin(r0, r1, ep, gp.zero);
      wg_wait<1>();
      tile_step(dw, desc_x(b_x(7) + 1), desc_w(b_w(7), 4));
      g0.part<PS + PS2, 24>(d0, r0, r1);
      sts64f(sb + OFF_RS1 + p * 8, r0, r1);
      cin_begin(c, sb, 1, slot_of(1, 0), xA, accA, z);
      if (p < 4) mbar_arrive(ev_bar(bars, EV_END));
#pragma unroll
      for (int i = 0; i < 24; i++)
        sts128f(sb + p * 16 + (i < 16 ? OFF_PARK + i * 2048 : OFF_PARK2 + (i - 16) * 2048), dw[4 * i], dw[4 * i + 1], dw[4 * i + 2], dw[4 * i + 3]);
      __syncwarp();
      if (lane == 0) mbar_arrive(bars + 8 * BAR_PARK);
    }
    if (!role(1)) {
      cin_begin(c, sb, wg, OFF_GIDX + wg * XSLOT, xA, accA, z);
      sts128f(sb + OFF_RS0 + p * 16, r0, r1, r2, r3);
      __syncwarp();
      if (lane == 0) mbar_arrive(bars + 8 * BAR_PARK);
    }

    {
    int cta, tid;
    asm volatile("mov.u32 %0, %%ctaid.x;" : "=r"(cta));
    asm volatile("mov.u32 %0, %%tid.x;" : "=r"(tid));
    cta = __shfl_sync(0xffffffffu, cta, 0);
    const bool gemm = cta < NGEMM;
    const int p = tid & 127, wg = __shfl_sync(0xffffffffu, tid >> 7, 0);
    const int ncin = cin_count(cta);
    const int n0 = gemm ? NC_WG0 : NC_EXTRA / 2;
    const int rb = wg ? n0 : 0;
    const int nj = wg ? ncin - n0 : n0;
    cin_setup(c, sb, wg, p, gemm, nj, gp.zero);
    uint32_t fa = sb + (gemm ? slot_of(wg, (p >> 3) + 1) + NF * 128 : (wg ? XOFF_CIN1 : XOFF_CIN0) + (p >> 3) * CROW) + (p & 7) * 16, fd = sb + OFF_DNN + rb * 8;
    asm volatile("" : "+r"(fa), "+r"(fd));
    auto wg_sync = [&]() { if (wg == 0) bar_sync<1, 128>(); else bar_sync<3, 128>(); };
    auto result = [&](int r, bool on) {
      const uint32_t a = fa + (r & ~15) * CROW;
      const float4 v0 = lds128f(a), v1 = lds128f(a + 128), v2 = lds128f(a + 256), v3 = lds128f(a + 384);
      const int2 dn = lds64(fd + r * 8);
      float s = (((v0.x + v0.y) + (v0.z + v0.w)) + ((v1.x + v1.y) + (v1.z + v1.w))) +
                (((v2.x + v2.y) + (v2.z + v2.w)) + ((v3.x + v3.y) + (v3.z + v3.w)));
      s += __shfl_xor_sync(0xffffffffu, s, 1);
      s += __shfl_xor_sync(0xffffffffu, s, 2);
      s += __shfl_xor_sync(0xffffffffu, s, 4);
      if ((p & 7) == 0 && on) out[dn.y] = __float2bfloat16(s + __int_as_float(dn.x));
    };
    mbar_wait(gemm ? bars + 8 * BAR_GDONE : ev_bar(bars, EV_END), 0);
    cin_run(c, nj, xA, accA, z, [&]() {
      mbar_wait(bars + 8 * BAR_DNN, 0);
    }, [&](int j) {
    });
    wg_sync();
#pragma unroll 1
    for (int r = p >> 3; r < ((nj + 15) & ~15); r += 16) result(r, r < nj);
    }
  }
}

typedef CUresult (*EncodeFn)(CUtensorMap*, CUtensorMapDataType, cuuint32_t, void*, const cuuint64_t*, const cuuint64_t*,
                             const cuuint32_t*, const cuuint32_t*, CUtensorMapInterleave, CUtensorMapSwizzle,
                             CUtensorMapL2promotion, CUtensorMapFloatOOBfill);

extern "C" void kernel_launch(void* const* d_in, const int* in_sizes, int n_in, void* d_out, int out_size) {
  void* fn = nullptr;
  cudaDriverEntryPointQueryResult q;
  cudaGetDriverEntryPoint("cuTensorMapEncodeTiled", &fn, cudaEnableDefault, &q);
  EncodeFn enc = (EncodeFn)fn;
  CUtensorMap tmW, tmT, tmS, tmC;
  const cuuint32_t es[3] = {1, 1, 1};
  {
    cuuint64_t dims[2] = {DIN, DIN}, st[1] = {DIN * 2};
    cuuint32_t box[2] = {64, 64};
    enc(&tmW, CU_TENSOR_MAP_DATA_TYPE_BFLOAT16, 2, d_in[4], dims, st, box, es, CU_TENSOR_MAP_INTERLEAVE_NONE,
        CU_TENSOR_MAP_SWIZZLE_128B, CU_TENSOR_MAP_L2_PROMOTION_NONE, CU_TENSOR_MAP_FLOAT_OOB_FILL_NONE);
  }
  {
    cuuint64_t dims[2] = {64, (cuuint64_t)(in_sizes[1] / 64)}, st[1] = {128};
    cuuint32_t box[2] = {64, 1};
    enc(&tmT, CU_TENSOR_MAP_DATA_TYPE_BFLOAT16, 2, d_in[1], dims, st, box, es, CU_TENSOR_MAP_INTERLEAVE_NONE,
        CU_TENSOR_MAP_SWIZZLE_128B, CU_TENSOR_MAP_L2_PROMOTION_NONE, CU_TENSOR_MAP_FLOAT_OOB_FILL_NONE);
  }
  void* x0 = nullptr;
  cudaGetSymbolAddress(&x0, g_x0);
  {
    cuuint64_t dims[2] = {FS * 64, NB}, st[1] = {FS * 128};
    cuuint32_t box[2] = {64, NC_GEMM + 1};
    enc(&tmS, CU_TENSOR_MAP_DATA_TYPE_BFLOAT16, 2, x0, dims, st, box, es, CU_TENSOR_MAP_INTERLEAVE_NONE,
        CU_TENSOR_MAP_SWIZZLE_128B, CU_TENSOR_MAP_L2_PROMOTION_NONE, CU_TENSOR_MAP_FLOAT_OOB_FILL_NONE);
  }
  {
    cuuint64_t dims[2] = {64, NB * FS}, st[1] = {128};
    cuuint32_t box[2] = {64, FS};
    enc(&tmC, CU_TENSOR_MAP_DATA_TYPE_BFLOAT16, 2, x0, dims, st, box, es, CU_TENSOR_MAP_INTERLEAVE_NONE,
        CU_TENSOR_MAP_SWIZZLE_128B, CU_TENSOR_MAP_L2_PROMOTION_NONE, CU_TENSOR_MAP_FLOAT_OOB_FILL_NONE);
  }
  GPtr gp;
  gp.zero = 0;
  cudaGetSymbolAddress((void**)&gp.s, g_scratch);
  cudaGetSymbolAddress((void**)&gp.tab, g_slot_tab);
  cudaFuncSetAttribute(xdeepfm_kernel, cudaFuncAttributeMaxDynamicSharedMemorySize, SMEM_BYTES);
  xdeepfm_kernel<<<GRID, 384, SMEM_BYTES, cudaStreamPerThread>>>(
      (const int*)d_in[0], (const __nv_bfloat16*)d_in[1], (const __nv_bfloat16*)d_in[4], (const __nv_bfloat16*)d_in[5],
      (const __nv_bfloat16*)d_in[6], (const __nv_bfloat16*)d_in[2], (const __nv_bfloat16*)d_in[3],
      (const __nv_bfloat16*)d_in[7], (__nv_bfloat16*)d_out, gp, tmW, tmT, tmS, tmC);
}
```

```cpp
#include <cuda_runtime.h>
#include <cuda_bf16.h>
#include <cuda.h>
#include <stdint.h>

__device__ __forceinline__ void wgmma_ss_n256(float (&d)[96], float (&e)[32], uint64_t descA, uint64_t descB, int scaleD) {
  asm volatile("{\n.reg .pred p;\nsetp.ne.b32 p, %130, 0;\n"
      "wgmma.mma_async.sync.aligned.m64n256k16.f32.bf16.bf16 {"
      "%0, %1, %2, %3, %4, %5, %6, %7, %8, %9, %10, %11, %12, %13, %14, %15,"
      "%16, %17, %18, %19, %20, %21, %22, %23, %24, %25, %26, %27, %28, %29, %30, %31,"
      "%32, %33, %34, %35, %36, %37, %38, %39, %40, %41, %42, %43, %44, %45, %46, %47,"
      "%48, %49, %50, %51, %52, %53, %54, %55, %56, %57, %58, %59, %60, %61, %62, %63,"
      "%64, %65, %66, %67, %68, %69, %70, %71, %72, %73, %74, %75, %76, %77, %78, %79,"
      "%80, %81, %82, %83, %84, %85, %86, %87, %88, %89, %90, %91, %92, %93, %94, %95,"
      "%96, %97, %98, %99, %100, %101, %102, %103, %104, %105, %106, %107, %108, %109, %110, %111,"
      "%112, %113, %114, %115, %116, %117, %118, %119, %120, %121, %122, %123, %124, %125, %126, %127"
      "}, %128, %129, p, 1, 1, 0, 1;\n}\n"
      : "+f"(d[0]), "+f"(d[1]), "+f"(d[2]), "+f"(d[3]), "+f"(d[4]), "+f"(d[5]), "+f"(d[6]), "+f"(d[7]),
        "+f"(d[8]), "+f"(d[9]), "+f"(d[10]), "+f"(d[11]), "+f"(d[12]), "+f"(d[13]), "+f"(d[14]), "+f"(d[15]),
        "+f"(d[16]), "+f"(d[17]), "+f"(d[18]), "+f"(d[19]), "+f"(d[20]), "+f"(d[21]), "+f"(d[22]), "+f"(d[23]),
        "+f"(d[24]), "+f"(d[25]), "+f"(d[26]), "+f"(d[27]), "+f"(d[28]), "+f"(d[29]), "+f"(d[30]), "+f"(d[31]),
        "+f"(d[32]), "+f"(d[33]), "+f"(d[34]), "+f"(d[35]), "+f"(d[36]), "+f"(d[37]), "+f"(d[38]), "+f"(d[39]),
        "+f"(d[40]), "+f"(d[41]), "+f"(d[42]), "+f"(d[43]), "+f"(d[44]), "+f"(d[45]), "+f"(d[46]), "+f"(d[47]),
        "+f"(d[48]), "+f"(d[49]), "+f"(d[50]), "+f"(d[51]), "+f"(d[52]), "+f"(d[53]), "+f"(d[54]), "+f"(d[55]),
        "+f"(d[56]), "+f"(d[57]), "+f"(d[58]), "+f"(d[59]), "+f"(d[60]), "+f"(d[61]), "+f"(d[62]), "+f"(d[63]),
        "+f"(d[64]), "+f"(d[65]), "+f"(d[66]), "+f"(d[67]), "+f"(d[68]), "+f"(d[69]), "+f"(d[70]), "+f"(d[71]),
        "+f"(d[72]), "+f"(d[73]), "+f"(d[74]), "+f"(d[75]), "+f"(d[76]), "+f"(d[77]), "+f"(d[78]), "+f"(d[79]),
        "+f"(d[80]), "+f"(d[81]), "+f"(d[82]), "+f"(d[83]), "+f"(d[84]), "+f"(d[85]), "+f"(d[86]), "+f"(d[87]),
        "+f"(d[88]), "+f"(d[89]), "+f"(d[90]), "+f"(d[91]), "+f"(d[92]), "+f"(d[93]), "+f"(d[94]), "+f"(d[95]),
        "+f"(e[0]), "+f"(e[1]), "+f"(e[2]), "+f"(e[3]), "+f"(e[4]), "+f"(e[5]), "+f"(e[6]), "+f"(e[7]),
        "+f"(e[8]), "+f"(e[9]), "+f"(e[10]), "+f"(e[11]), "+f"(e[12]), "+f"(e[13]), "+f"(e[14]), "+f"(e[15]),
        "+f"(e[16]), "+f"(e[17]), "+f"(e[18]), "+f"(e[19]), "+f"(e[20]), "+f"(e[21]), "+f"(e[22]), "+f"(e[23]),
        "+f"(e[24]), "+f"(e[25]), "+f"(e[26]), "+f"(e[27]), "+f"(e[28]), "+f"(e[29]), "+f"(e[30]), "+f"(e[31])
      : "l"(descA), "l"(descB), "r"(scaleD));
}
__device__ __forceinline__ void wgmma_ss_n192(float (&d)[96], uint64_t descA, uint64_t descB, int scaleD) {
  asm volatile("{\n.reg .pred p;\nsetp.ne.b32 p, %98, 0;\n"
      "wgmma.mma_async.sync.aligned.m64n192k16.f32.bf16.bf16 {"
      "%0, %1, %2, %3, %4, %5, %6, %7, %8, %9, %10, %11, %12, %13, %14, %15,"
      "%16, %17, %18, %19, %20, %21, %22, %23, %24, %25, %26, %27, %28, %29, %30, %31,"
      "%32, %33, %34, %35, %36, %37, %38, %39, %40, %41, %42, %43, %44, %45, %46, %47,"
      "%48, %49, %50, %51, %52, %53, %54, %55, %56, %57, %58, %59, %60, %61, %62, %63,"
      "%64, %65, %66, %67, %68, %69, %70, %71, %72, %73, %74, %75, %76, %77, %78, %79,"
      "%80, %81, %82, %83, %84, %85, %86, %87, %88, %89, %90, %91, %92, %93, %94, %95"
      "}, %96, %97, p, 1, 1, 0, 1;\n}\n"
      : "+f"(d[0]), "+f"(d[1]), "+f"(d[2]), "+f"(d[3]), "+f"(d[4]), "+f"(d[5]), "+f"(d[6]), "+f"(d[7]),
        "+f"(d[8]), "+f"(d[9]), "+f"(d[10]), "+f"(d[11]), "+f"(d[12]), "+f"(d[13]), "+f"(d[14]), "+f"(d[15]),
        "+f"(d[16]), "+f"(d[17]), "+f"(d[18]), "+f"(d[19]), "+f"(d[20]), "+f"(d[21]), "+f"(d[22]), "+f"(d[23]),
        "+f"(d[24]), "+f"(d[25]), "+f"(d[26]), "+f"(d[27]), "+f"(d[28]), "+f"(d[29]), "+f"(d[30]), "+f"(d[31]),
        "+f"(d[32]), "+f"(d[33]), "+f"(d[34]), "+f"(d[35]), "+f"(d[36]), "+f"(d[37]), "+f"(d[38]), "+f"(d[39]),
        "+f"(d[40]), "+f"(d[41]), "+f"(d[42]), "+f"(d[43]), "+f"(d[44]), "+f"(d[45]), "+f"(d[46]), "+f"(d[47]),
        "+f"(d[48]), "+f"(d[49]), "+f"(d[50]), "+f"(d[51]), "+f"(d[52]), "+f"(d[53]), "+f"(d[54]), "+f"(d[55]),
        "+f"(d[56]), "+f"(d[57]), "+f"(d[58]), "+f"(d[59]), "+f"(d[60]), "+f"(d[61]), "+f"(d[62]), "+f"(d[63]),
        "+f"(d[64]), "+f"(d[65]), "+f"(d[66]), "+f"(d[67]), "+f"(d[68]), "+f"(d[69]), "+f"(d[70]), "+f"(d[71]),
        "+f"(d[72]), "+f"(d[73]), "+f"(d[74]), "+f"(d[75]), "+f"(d[76]), "+f"(d[77]), "+f"(d[78]), "+f"(d[79]),
        "+f"(d[80]), "+f"(d[81]), "+f"(d[82]), "+f"(d[83]), "+f"(d[84]), "+f"(d[85]), "+f"(d[86]), "+f"(d[87]),
        "+f"(d[88]), "+f"(d[89]), "+f"(d[90]), "+f"(d[91]), "+f"(d[92]), "+f"(d[93]), "+f"(d[94]), "+f"(d[95])
      : "l"(descA), "l"(descB), "r"(scaleD));
}
template <unsigned long long DESC, int SCALE>
__device__ __forceinline__ void wgmma_rs_n56(float (&d)[28], uint32_t a0, uint32_t a1, uint32_t a2, uint32_t a3) {
  asm volatile("{\n.reg .b64 desc;\nmov.b64 desc, %32;\n"
      "wgmma.mma_async.sync.aligned.m64n56k16.f32.bf16.bf16 {"
      "%0, %1, %2, %3, %4, %5, %6, %7, %8, %9, %10, %11, %12, %13, %14, %15,"
      "%16, %17, %18, %19, %20, %21, %22, %23, %24, %25, %26, %27"
      "}, {%28, %29, %30, %31}, desc, %33, 1, 1, 0;\n}\n"
      : "+f"(d[0]), "+f"(d[1]), "+f"(d[2]), "+f"(d[3]), "+f"(d[4]), "+f"(d[5]), "+f"(d[6]), "+f"(d[7]),
        "+f"(d[8]), "+f"(d[9]), "+f"(d[10]), "+f"(d[11]), "+f"(d[12]), "+f"(d[13]), "+f"(d[14]), "+f"(d[15]),
        "+f"(d[16]), "+f"(d[17]), "+f"(d[18]), "+f"(d[19]), "+f"(d[20]), "+f"(d[21]), "+f"(d[22]), "+f"(d[23]),
        "+f"(d[24]), "+f"(d[25]), "+f"(d[26]), "+f"(d[27])
      : "r"(a0), "r"(a1), "r"(a2), "r"(a3), "n"(DESC), "n"(SCALE));
}
template <unsigned long long DESC, int SCALE>
__device__ __forceinline__ void wgmma_rs_n32(float (&d)[28], uint32_t a0, uint32_t a1, uint32_t a2, uint32_t a3) {
  asm volatile("{\n.reg .b64 desc;\nmov.b64 desc, %20;\n"
      "wgmma.mma_async.sync.aligned.m64n32k16.f32.bf16.bf16 {"
      "%0, %1, %2, %3, %4, %5, %6, %7, %8, %9, %10, %11, %12, %13, %14, %15"
      "}, {%16, %17, %18, %19}, desc, %21, 1, 1, 0;\n}\n"
      : "+f"(d[0]), "+f"(d[1]), "+f"(d[2]), "+f"(d[3]), "+f"(d[4]), "+f"(d[5]), "+f"(d[6]), "+f"(d[7]),
        "+f"(d[8]), "+f"(d[9]), "+f"(d[10]), "+f"(d[11]), "+f"(d[12]), "+f"(d[13]), "+f"(d[14]), "+f"(d[15])
      : "r"(a0), "r"(a1), "r"(a2), "r"(a3), "n"(DESC), "n"(SCALE));
}

constexpr int NB = 4096, NF = 26, DIN = 1664;
constexpr int NGEMM = 128, NEXTRA = 4, GRID = NGEMM + NEXTRA;
constexpr int NC_EXTRA = 84;
constexpr int NC_WG0 = 16;
constexpr int HK = 4;
constexpr int PE0 = 9;
constexpr int WD = 2;
constexpr int GI = 3;
constexpr int PE1 = 4;
constexpr int PE2 = 8;
constexpr int PS2 = 6;
constexpr int POLL = 400;
constexpr int BGN = 1;
constexpr int PREG = 40;
constexpr int PS = 6;
constexpr int RB = 4;
constexpr int NC_GEMM = 29, NBIG = NB - NGEMM * NC_GEMM - NEXTRA * NC_EXTRA;
static_assert(NBIG >= 0 && NBIG <= NGEMM && NC_EXTRA % 4 == 0 && NC_EXTRA <= 96, "split");
constexpr int CW_MAIN = 22 * 1792, CW_LIN = 2 * 1024, CW_BYTES = CW_MAIN + CW_LIN;
constexpr int XSLOT = 4096;

constexpr int UNIT = 8192, FS = 18;
constexpr int U_W = 6, U_XB = 18, U_SP = 24;
constexpr int CW_CUT = 9;
constexpr int OFF_CW = 0, OFF_CW2 = 6 * UNIT, OFF_CWL = 9 * UNIT;
constexpr int CROW = 528;
constexpr int OFF_PARK = 10 * UNIT, OFF_PARK2 = 24 * UNIT;
constexpr int OFF_RS0 = OFF_CWL + CW_LIN, OFF_RS1 = OFF_CWL - 1024;
constexpr int OFF_GIDX = 26 * UNIT;
constexpr int OFF_TIDX = OFF_GIDX + 128 * NF * 4 - 8 * 64 * 4;
constexpr int OFF_CIDX = OFF_GIDX + 128 * NF * 4;
constexpr int OFF_EPI = OFF_CIDX + 32 * 8 * 4;
constexpr int OFF_DNN = OFF_EPI + 128 * 16;
constexpr int OFF_BAR = OFF_DNN + 112 * 8;
constexpr int SMEM_BYTES = OFF_BAR + 50 * 8;
static_assert(CW_CUT * 1792 <= 2 * UNIT && (22 - CW_CUT) * 1792 <= 3 * UNIT , "smem");
constexpr uint32_t SMEM_BASE = 1024;
static_assert(SMEM_BYTES <= 232448, "smem");
static_assert(OFF_EPI % 16 == 0 && OFF_BAR % 8 == 0, "align");
constexpr int XOFF_W3 = 0, XOFF_W2 = 35152, XOFF_W1 = 70304, XOFF_M = XOFF_W1 + 8 * 1352, XOFF_S = XOFF_M + 32 * 40 * 4,
              XOFF_SLOT = 10 * UNIT, XOFF_CIN0 = 2 * UNIT, XOFF_CIN1 = 18 * UNIT, XOFF_CIDX = 22 * UNIT,
              XOFF_BAR = 24 * UNIT, NPAIR = NC_EXTRA / 4;
static_assert(XOFF_S + 14 * 3136 <= 21 * UNIT && 48 * CROW <= 4 * UNIT, "smem");

constexpr int BAR_PARK = 7,
              BAR_FULL = 8,
              BAR_EV = 16,
              BAR_CW = 24,
              BAR_GIDX = 25,
              BAR_X0 = 26,
              BAR_W0 = 27,
              BAR_DNN = 28,
              BAR_T = 29,
              BAR_GDONE = 30,
              BAR_EPOCH = 31,
              BAR_CFULL = 32,
              BAR_C0 = 48;
constexpr int EV_CW = 29, EV_SLOT = 30, EV_END = 33;
__device__ __forceinline__ uint32_t ev_bar(uint32_t bars, int e) { return bars + 8 * (BAR_EV + (e & 7)); }
__device__ __forceinline__ uint32_t ev_par(int e) { return (e >> 3) & 1; }
constexpr unsigned long long STAGES = 0xb4b4924924924ull;
__host__ __device__ constexpr int b_x(int t) { return ((0xb2c1430bu >> (4 * t)) & 15) * 2; }
__host__ __device__ constexpr int b_w(int t) { return (0x0d0a120eu >> (8 * (t & 3))) & 31; }
__host__ __device__ constexpr int b_ws(int t) { return (t & 3) == 3 ? 4 : 1; }

struct Scratch {
  uint4 cw[CW_BYTES / 16];
  uint2 part[8 * NB];
  unsigned epoch[GRID];
  unsigned foldflag;
};
__device__ __align__(128) Scratch g_scratch;
__device__ __align__(1024) __nv_bfloat16 g_x0[NB * FS * 64];
struct GPtr { Scratch* s; const uint4* tab; uint32_t zero; };

__device__ __forceinline__ void wg_fence() { asm volatile("wgmma.fence.sync.aligned;" ::: "memory"); }
__device__ __forceinline__ void wg_commit() { asm volatile("wgmma.commit_group.sync.aligned;" ::: "memory"); }
template <int N> __device__ __forceinline__ void wg_wait() { asm volatile("wgmma.wait_group.sync.aligned %0;" ::"n"(N) : "memory"); }
__device__ __forceinline__ uint64_t mkdesc(uint32_t addr, uint32_t lbo, uint32_t sbo, uint32_t swz) {
  return (uint64_t)((addr & 0x3FFFF) >> 4) | ((uint64_t)(lbo >> 4) << 16) | ((uint64_t)(sbo >> 4) << 32) | ((uint64_t)swz << 62);
}
__device__ __forceinline__ bool elect1() {
  uint32_t p; asm volatile("{\n.reg .pred p;\nelect.sync _|p, 0xffffffff;\nselp.b32 %0, 1, 0, p;\n}" : "=r"(p)); return p;
}
__device__ __forceinline__ int fresh(int v) { asm volatile("" : "+r"(v)); return v; }
__device__ __forceinline__ void mbar_init(uint32_t bar, uint32_t cnt) { asm volatile("mbarrier.init.shared::cta.b64 [%0], %1;" ::"r"(bar), "r"(cnt) : "memory"); }
__device__ __forceinline__ void mbar_arrive(uint32_t bar) { asm volatile("mbarrier.arrive.shared::cta.b64 _, [%0];" ::"r"(bar) : "memory"); }
__device__ __forceinline__ void mbar_arrive_cta(uint32_t bar, uint32_t cta) {
  asm volatile("{\n.reg .b32 r;\nmapa.shared::cluster.u32 r, %0, %1;\nmbarrier.arrive.shared::cluster.b64 _, [r];\n}" ::"r"(bar), "r"(cta) : "memory");
}
__device__ __forceinline__ void mbar_expect_tx(uint32_t bar, uint32_t bytes) { asm volatile("mbarrier.arrive.expect_tx.shared::cta.b64 _, [%0], %1;" ::"r"(bar), "r"(bytes) : "memory"); }
__device__ __forceinline__ void mbar_wait(uint32_t bar, uint32_t parity) {
  asm volatile("{\n.reg .pred p;\nLAB_WAIT:\n"
               "mbarrier.try_wait.parity.shared::cta.b64 p, [%0], %1;\n"
               "@!p bra LAB_WAIT;\n}" ::"r"(bar), "r"(parity) : "memory");
}
__device__ __forceinline__ void flag_wait(const unsigned* p, unsigned target, unsigned sleep_ns) {
  asm volatile("{\n.reg .pred p;\n.reg .u32 n, v;\nmov.u32 n, 0;\nLAB_WAIT:\n"
               "ld.acquire.gpu.global.u32 v, [%0];\n"
               "sub.u32 v, v, %1;\n"
               "setp.ge.s32 p, v, 0;\n"
               "@p bra DONE;\n"
               "nanosleep.u32 %2;\n"
               "add.u32 n, n, 1;\n"
               "setp.lt.u32 p, n, 400000;\n"
               "@p bra LAB_WAIT;\n"
               "DONE:\n}" ::"l"(p), "r"(target), "r"(sleep_ns) : "memory");
}
__device__ __forceinline__ void put_tagged(uint2* p, float v, unsigned tag) {
  asm volatile("st.relaxed.gpu.global.v2.b32 [%0], {%1, %2};" ::"l"(p), "r"(__float_as_uint(v)), "r"(tag) : "memory");
}
__device__ __forceinline__ void flag_add(unsigned* p) { asm volatile("red.release.gpu.global.add.u32 [%0], 1;" ::"l"(p) : "memory"); }
__device__ __forceinline__ void tma_load(uint32_t dst, const CUtensorMap* tm, int c0, int c1, uint32_t bar) {
  asm volatile("cp.async.bulk.tensor.2d.shared::cluster.global.mbarrier::complete_tx::bytes [%0], [%1, {%3, %4}], [%2];"
               ::"r"(dst), "l"(tm), "r"(bar), "r"(c0), "r"(c1) : "memory");
}
__device__ __forceinline__ void tma_row_mc(uint32_t dst, const CUtensorMap* tm, int row, uint32_t bar) {
  asm volatile("cp.async.bulk.tensor.2d.shared::cluster.global.mbarrier::complete_tx::bytes.multicast::cluster [%0], [%1, {%3, %4}], [%2], %5;"
               ::"r"(dst), "l"(tm), "r"(bar), "r"(0), "r"(row), "h"((uint16_t)3));
}
__device__ __forceinline__ void tma_row(uint32_t dst, const CUtensorMap* tm, int row, uint32_t bar) {
  asm volatile("cp.async.bulk.tensor.2d.shared::cluster.global.mbarrier::complete_tx::bytes [%0], [%1, {%3, %4}], [%2];"
               ::"r"(dst), "l"(tm), "r"(bar), "r"(0), "r"(row));
}
__device__ __forceinline__ void tma_store(const CUtensorMap* tm, int c0, int c1, uint32_t src) {
  asm volatile("cp.async.bulk.tensor.2d.global.shared::cta.bulk_group [%0, {%1, %2}], [%3];\ncp.async.bulk.commit_group;"
               ::"l"(tm), "r"(c0), "r"(c1), "r"(src) : "memory");
}
template <int N> __device__ __forceinline__ void store_read() { asm volatile("cp.async.bulk.wait_group.read %0;" ::"n"(N) : "memory"); }
__device__ __forceinline__ void bulk_load(uint32_t dst, const void* src, uint32_t bytes, uint32_t bar) {
  asm volatile("cp.async.bulk.shared::cluster.global.mbarrier::complete_tx::bytes [%0], [%1], %2, [%3];"
               ::"r"(dst), "l"(src), "r"(bytes), "r"(bar));
}
__device__ __forceinline__ void l2_prefetch(const void* src, uint32_t bytes) {
  asm volatile("cp.async.bulk.prefetch.L2.global [%0], %1;" ::"l"(src), "r"(bytes));
}
__device__ __forceinline__ void w_prefetch(const __nv_bfloat16* w1, int f, int cta, int piece) {
  l2_prefetch(w1 + (f * 64 + (cta >> 3) * 4 + (cta & 1) * 2 + (piece & 1)) * DIN + (piece < 2 ? (cta & 6) * 192 : 1536 + (cta & 4) * 16),
              piece < 2 ? 768 : 128);
}
__device__ __forceinline__ void cpasync16(uint32_t dst, const void* src) {
  asm volatile("cp.async.cg.shared.global [%0], [%1], 16;" ::"r"(dst), "l"(src) : "memory");
}
template <int ID, int N> __device__ __forceinline__ void bar_sync() { asm volatile("bar.sync %0, %1;" ::"n"(ID), "n"(N) : "memory"); }
template <int ID, int N> __device__ __forceinline__ void bar_arrive() { asm volatile("bar.arrive %0, %1;" ::"n"(ID), "n"(N) : "memory"); }
__device__ __forceinline__ void ldsm4t(uint32_t& a, uint32_t& b, uint32_t& c, uint32_t& d, uint32_t addr) {
  asm volatile("ldmatrix.sync.aligned.m8n8.x4.trans.shared.b16 {%0,%1,%2,%3}, [%4];" : "=r"(a), "=r"(b), "=r"(c), "=r"(d) : "r"(addr) : "memory");
}
__device__ __forceinline__ int lds32(uint32_t addr) { int v; asm volatile("ld.shared.b32 %0, [%1];" : "=r"(v) : "r"(addr)); return v; }
__device__ __forceinline__ int2 lds64(uint32_t addr) { int2 v; asm volatile("ld.shared.v2.b32 {%0,%1}, [%2];" : "=r"(v.x), "=r"(v.y) : "r"(addr)); return v; }
__device__ __forceinline__ int4 lds128(uint32_t addr) {
  int4 v; asm volatile("ld.shared.v4.b32 {%0,%1,%2,%3}, [%4];" : "=r"(v.x), "=r"(v.y), "=r"(v.z), "=r"(v.w) : "r"(addr)); return v;
}
__device__ __forceinline__ float4 lds128f(uint32_t addr) {
  float4 v; asm volatile("ld.shared.v4.f32 {%0,%1,%2,%3}, [%4];" : "=f"(v.x), "=f"(v.y), "=f"(v.z), "=f"(v.w) : "r"(addr) : "memory"); return v;
}
__device__ __forceinline__ float4 lds128f(uint32_t addr, uint32_t off) {
  float4 v;
  asm volatile("{\n.reg .u32 t;\nadd.u32 t, %4, %5;\nld.shared.v4.f32 {%0,%1,%2,%3}, [t];\n}" : "=f"(v.x), "=f"(v.y), "=f"(v.z), "=f"(v.w) : "r"(addr), "r"(off) : "memory");
  return v;
}
__device__ __forceinline__ void sts32f(uint32_t addr, float v) { asm volatile("st.shared.f32 [%0], %1;" ::"r"(addr), "f"(v) : "memory"); }
__device__ __forceinline__ float bf_lo(uint32_t v) { return __uint_as_float(v << 16); }
__device__ __forceinline__ float bf_hi(uint32_t v) { return __uint_as_float(v & 0xffff0000u); }
__device__ __forceinline__ float bf2f(__nv_bfloat16 v) { return __bfloat162float(v); }

__device__ __forceinline__ uint32_t mul2(uint32_t a, uint32_t b) {
  uint32_t r; asm volatile("mul.rn.bf16x2 %0, %1, %2;" : "=r"(r) : "r"(a), "r"(b)); return r;
}
__device__ __forceinline__ uint32_t mul2lo(uint32_t a, uint32_t b) {
  uint32_t r;
  asm volatile("{\n.reg .b16 l, h;\n.reg .b32 t;\nmov.b32 {l, h}, %2;\nmov.b32 t, {l, l};\nmul.rn.bf16x2 %0, %1, t;\n}" : "=r"(r) : "r"(a), "r"(b));
  return r;
}
__device__ __forceinline__ uint32_t mul2hi(uint32_t a, uint32_t b) {
  uint32_t r;
  asm volatile("{\n.reg .b16 l, h;\n.reg .b32 t;\nmov.b32 {l, h}, %2;\nmov.b32 t, {h, h};\nmul.rn.bf16x2 %0, %1, t;\n}" : "=r"(r) : "r"(a), "r"(b));
  return r;
}

__host__ __device__ constexpr int xfield(int r, int e, int c) {
  return r == 9 ? 24 + e : 8 * (r / 3) + 2 * (((r % 3) + c) & 3) + (((r % 3) == 2 && c >= 2) ? 1 - e : e);
}
__host__ __device__ constexpr int blk_a(int b) { return b < 12 ? 3 * (b / 8) + ((b & 3) == 3) : (b < 15 ? 3 * (b - 12) : 3 * (b - 15)); }
__host__ __device__ constexpr int blk_b(int b) { return b < 12 ? 3 * (b < 4 ? 1 : 2) + ((b & 3) == 3 ? 0 : (b & 3)) : (b < 15 ? 3 * (b - 12) + 1 : 9); }
__host__ __device__ constexpr int slot_pq(int u, int e, int c) {
  return u < 36 ? (xfield(blk_a(u >> 1), e, c) | (xfield(blk_b(u >> 1), u & 1, c) << 8))
       : u < 39 ? (xfield(3 * (u - 36), e, c) * 257)
       : u < 42 ? (xfield(3 * (u - 39), e, c) | (xfield(3 * (u - 39) + 2, e, c) << 8))
       : u == 42 ? (xfield(3 * e, 0, c) | (xfield(3 * e, 1, c) << 8))
       : u == 43 ? (e == 0 ? (xfield(6, 0, c) | (xfield(6, 1, c) << 8))
                           : (c == 0 ? 24 * 257 : c == 1 ? 25 * 257 : c == 2 ? (24 | 25 << 8) : 26 * 257))
       : u < 47 ? (xfield(3 * (u - 44), e, c) | (26 << 8))
       : (c == 0 ? ((24 + e) | 26 << 8) : 27 * 257);
}
struct SlotTab { uint32_t v[48 * 8]; };
constexpr SlotTab make_slot_tab() {
  SlotTab t{};
  for (int u = 0; u < 48; u++)
    for (int k = 0; k < 8; k++) {
      const int pq = slot_pq(u, k & 1, k >> 1), p = pq & 255, q = pq >> 8;
      t.v[u * 8 + k] = (uint32_t)((p * 28 + q) * 4) | ((uint32_t)(((p != q && q < 26) ? q * 28 + p : 27 * 28 + 27) * 4) << 16);
    }
  return t;
}
__device__ __align__(16) const SlotTab g_slot_tab = make_slot_tab();

struct CinCtx {
  uint32_t o03, o14, o25, o69, o78, cin, selA, selB;
  bool ones, lead;
  uint32_t so, so2, co, co2, bar, jump, dslot, last;
  bool ring;
};
constexpr unsigned long long CW_DESC = (unsigned long long)((SMEM_BASE + OFF_CW) >> 4) | (8ull << 16) | (16ull << 32);
constexpr unsigned long long CWL_DESC = CW_DESC + (OFF_CWL - OFF_CW) / 16;

template <int U>
__device__ __forceinline__ uint32_t zreg(const uint32_t (&x)[10][2], int h, const CinCtx& c) {
  if constexpr (U < 36) {
    if constexpr (U & 1) return mul2hi(x[blk_a(U >> 1)][h], x[blk_b(U >> 1)][h]);
    else return mul2lo(x[blk_a(U >> 1)][h], x[blk_b(U >> 1)][h]);
  } else if constexpr (U < 39) {
    return mul2(x[3 * (U - 36)][h], x[3 * (U - 36)][h]);
  } else if constexpr (U < 42) {
    return mul2(x[3 * (U - 39)][h], x[3 * (U - 39) + 2][h]);
  } else if constexpr (U == 42) {
    return mul2(__byte_perm(x[0][h], x[3][h], 0x5410), __byte_perm(x[0][h], x[3][h], 0x7632));
  } else {
    const uint32_t f = c.ones ? 0x3f803f80u : x[9][h];
    return mul2(__byte_perm(x[6][h], f, c.selA), __byte_perm(x[6][h], f, c.selB));
  }
}

template <int G>
__device__ __forceinline__ void z_fill(uint32_t (&z)[8], const uint32_t (&x)[10][2], const CinCtx& c) {
  z[0] = zreg<4 * G>(x, 0, c);     z[1] = zreg<4 * G>(x, 1, c);
  z[2] = zreg<4 * G + 1>(x, 0, c); z[3] = zreg<4 * G + 1>(x, 1, c);
  z[4] = zreg<4 * G + 2>(x, 0, c); z[5] = zreg<4 * G + 2>(x, 1, c);
  z[6] = zreg<4 * G + 3>(x, 0, c); z[7] = zreg<4 * G + 3>(x, 1, c);
}
__host__ __device__ constexpr unsigned long long cw_desc(int s) { return CW_DESC + (s < CW_CUT ? s * 1792 : OFF_CW2 - OFF_CW + (s - CW_CUT) * 1792) / 16; }
template <int G>
__device__ __forceinline__ void z_mma(float (&acc)[28], const uint32_t (&z)[8]) {
  wgmma_rs_n56<cw_desc(2 * G), G != 0>(acc, z[0], z[1], z[2], z[3]);
  wgmma_rs_n56<cw_desc(2 * G + 1), 1>(acc, z[4], z[5], z[6], z[7]);
}

__device__ __forceinline__ void cin_finish(const CinCtx& c, float (&acc)[28], uint32_t out) {
#pragma unroll
  for (int i = 0; i < 28; i++) asm volatile("" : "+f"(acc[i]));
  float s0 = acc[12] * acc[13], s1 = acc[14] * acc[15];
#pragma unroll
  for (int i = 0; i < 12; i += 2) {
    s0 = fmaf(acc[i], acc[16 + i], s0);
    s1 = fmaf(acc[i + 1], acc[17 + i], s1);
  }
  sts32f(c.cin + out, s0 + s1);
}

__device__ __forceinline__ void cin_ldsm(const CinCtx& c, uint32_t so, uint32_t (&x)[10][2]) {
  ldsm4t(x[0][0], x[0][1], x[3][0], x[3][1], so + c.o03);
  ldsm4t(x[1][0], x[1][1], x[4][0], x[4][1], so + c.o14);
  ldsm4t(x[2][0], x[2][1], x[5][0], x[5][1], so + c.o25);
  ldsm4t(x[6][0], x[6][1], x[9][0], x[9][1], so + c.o69);
  ldsm4t(x[7][0], x[7][1], x[8][0], x[8][1], so + c.o78);
}
__device__ __forceinline__ void cin_load(const CinCtx& c, int k, bool real, uint32_t (&x)[10][2]) {
  if (k == 0 && real) mbar_wait(c.bar, 0);
  cin_ldsm(c, k ? c.so2 : c.so, x);
  if (k == 1 && c.lead) mbar_arrive(c.bar + 8 * NPAIR);
}
__device__ __forceinline__ void cin_advance(CinCtx& c) {
  const uint32_t d = c.so == c.jump ? c.dslot : 2 * XSLOT;
  c.so += d; c.so2 += d;
  c.co = c.ring ? c.co + 2 * CROW : c.so;
  c.bar += 8;
}
constexpr int CG_WAIT = 2;
constexpr int CG_FIN = 2;
constexpr int CG_HEAD = 3;
constexpr int CG_LIN = 3;
constexpr int CG_LOAD = 5;
constexpr int CG_N = 11;
static_assert(CG_FIN >= CG_WAIT && CG_FIN < CG_HEAD && CG_LOAD >= CG_HEAD && CG_LIN >= CG_HEAD && CG_LOAD < 10, "CIN schedule");
template <int G, int GEND, typename F>
__device__ __forceinline__ void cin_groups(const CinCtx& c, const uint32_t (&x)[10][2], float (&acc)[28], uint32_t (&z)[8],
                                           int q, bool more, uint32_t (&xn)[10][2], F finish) {
  if constexpr (G < GEND) {
    wg_fence();
    if constexpr (G == CG_LIN) {
      wgmma_rs_n32<CWL_DESC, 1>(acc, x[0][0], x[0][1], x[3][0], x[3][1]);
      wgmma_rs_n32<CWL_DESC + 1024 / 16, 1>(acc, x[6][0], x[6][1], x[9][0], x[9][1]);
    }
    z_mma<G>(acc, z);
    wg_commit();
    if constexpr (G == CG_LOAD) cin_load(c, q, more, xn);
    uint32_t zn[8];
    if constexpr (G + 1 < CG_N) z_fill<G + 1>(zn, x, c); else z_fill<0>(zn, xn, c);
    if constexpr (G == CG_FIN) finish();
    wg_wait<CG_WAIT>();
    if constexpr (G + 1 < GEND) cin_groups<G + 1, GEND>(c, x, acc, zn, q, more, xn, finish);
    else {
#pragma unroll
      for (int i = 0; i < 8; i++) z[i] = zn[i];
    }
    if constexpr (G + 1 < GEND) {
#pragma unroll
      for (int i = 0; i < 8; i++) z[i] = zn[i];
    }
  }
}
template <typename F>
__device__ __forceinline__ void cin_head(const CinCtx& c, uint32_t (&x)[10][2], float (&acc)[28], uint32_t (&z)[8], F finish) {
  cin_groups<0, CG_HEAD>(c, x, acc, z, 0, false, x, finish);
}
__device__ __forceinline__ void cin_tail(const CinCtx& c, const uint32_t (&x)[10][2], float (&acc)[28], uint32_t (&z)[8],
                                         int q, bool more, uint32_t (&xn)[10][2]) {
  cin_groups<CG_HEAD, CG_N>(c, x, acc, z, q, more, xn, []() {});
}

__device__ __forceinline__ int slot_of(int wg, int j) {
  return wg ? (j == 0 ? 9 * UNIT + XSLOT : j <= 8 ? 2 * UNIT + (j - 1) * XSLOT : 21 * UNIT + (j - 9) * XSLOT)
            : (j < 3 ? OFF_GIDX + j * XSLOT : 14 * UNIT + (j - 3) * XSLOT);
}

__device__ __forceinline__ void cin_begin(CinCtx& c, uint32_t sb, int wg, uint32_t first, uint32_t (&x)[10][2], float (&acc)[28], uint32_t (&z)[8]) {
  int t; asm volatile("mov.u32 %0, %%tid.x;" : "=r"(t));
  const int m = t & 16, f0 = t & 7, f1 = (f0 + 2) & 7, f2 = (f0 ^ 4) ^ (f0 >> 2);
  const uint32_t base = sb + m * 64, ch = (t & 96) + (t & 8) * 2;
  c.o03 = (base + f0 * 0x90) ^ ch;
  c.o14 = (base + f1 * 0x90) ^ ch;
  c.o25 = (base + f2 * 0x90) ^ ch;
  c.o69 = (base + 2048 + (m ? f0 & 1 : f0) * 0x90) ^ ch;
  c.o78 = m ? c.o25 + 1024 : c.o14 + 2048;
  mbar_wait(sb + OFF_BAR + 8 * BAR_GDONE, 0);
  mbar_wait(sb + OFF_BAR + 8 * (BAR_C0 + wg), 0);
  cin_ldsm(c, first, x);
  mbar_wait(sb + OFF_BAR + 8 * BAR_CW, 0);
  z_fill<0>(z, x, c);
  cin_head(c, x, acc, z, []() {});
}
__device__ __forceinline__ void cin_setup(CinCtx& c, uint32_t sb, int wg, int p, bool gemm, int nj, uint32_t zero) {
  c.bar = sb + (gemm ? OFF_BAR + 8 * (BAR_CFULL + wg * 8) : XOFF_BAR + wg * 16 * NPAIR);
  c.lead = (p & 31) == 0 && !gemm; c.ring = !gemm;
  c.so = !gemm ? XOFF_SLOT + 8 * wg * XSLOT : wg ? 2 * UNIT : OFF_GIDX + XSLOT;
  c.jump = c.so + (gemm && !wg ? 0 : 6 * XSLOT);
  c.dslot = !gemm ? -6 * XSLOT : wg ? 19 * UNIT - 6 * XSLOT : 14 * UNIT - OFF_GIDX - XSLOT;
  c.co = gemm ? c.so : (wg ? XOFF_CIN1 : XOFF_CIN0) - NF * 128;
  c.co2 = gemm ? XSLOT : CROW;
  c.so2 = c.so + XSLOT + zero;
  c.last = gemm ? slot_of(wg, (nj - 1) | 1) : c.co + ((nj - 1) & ~1) * CROW;
  c.cin = sb + NF * 128 + p * 4;
  const int q = p & 3;
  c.selA = q == 1 ? 0x7610 : 0x5410;
  c.selB = q == 0 ? 0x5432 : 0x7632;
  c.ones = q == 3;
}
template <typename F2, typename F3>
__device__ __forceinline__ void cin_run(CinCtx& c, int nj, uint32_t (&xA)[10][2], float (&accA)[28], uint32_t (&z)[8], F2 before_end, F3 st5) {
  float accB[28];
  uint32_t xB[10][2];
  const uint32_t lastA = nj & 1 ? c.last : 0;
#pragma unroll 1
  for (int j = 0;; j += 2) {
    cin_tail(c, xA, accA, z, 0, c.co != lastA, xB);
    if (c.co == lastA) { before_end(); wg_wait<0>(); cin_finish(c, accA, c.co); break; }
    cin_head(c, xB, accB, z, [&]() { st5(j); cin_finish(c, accA, c.co); });
    cin_tail(c, xB, accB, z, 1, true, xA);
    if (c.co == c.last) { before_end(); wg_wait<0>(); cin_finish(c, accB, c.co + c.co2); break; }
    cin_head(c, xA, accA, z, [&]() { st5(j + 1); cin_finish(c, accB, c.co + c.co2); });
    cin_advance(c);
  }
}

constexpr float ALPHA = 0.3292034911525734f, KAPPA = 2.423681954311584f;
__device__ __forceinline__ float gelu_acc(float v, float ab, float w, float s, float alpha = ALPHA) {
  const float a = fmaf(v, alpha, ab);
  const float u = a * fmaf(a, a, KAPPA);
  float th; asm("tanh.approx.f32 %0, %1;" : "=f"(th) : "f"(u));
  return fmaf(fmaf(a, th, a), w, s);
}

constexpr int QD = 2;
template <int NG>
struct Gelu {
  float4 q[QD + 1];
  uint32_t ep;
  __device__ __forceinline__ void start(uint32_t a) {
    ep = a;
#pragma unroll
    for (int i = 0; i < QD; i++) q[i] = lds128f(ep + i * 64);
  }
  template <int I0, int I1>
  __device__ __forceinline__ void part(float (&d)[4 * NG], float& r0, float& r1, uint32_t done) {
    float alpha;
    asm volatile("{\n.reg .pred p;\nmbarrier.test_wait.parity.shared::cta.b64 p, [%1], 0;\nselp.f32 %0, %2, 0f7FC00000, p;\n}"
                 : "=f"(alpha) : "r"(done), "f"(ALPHA) : "memory");
    part<I0, I1>(d, r0, r1, alpha);
  }
  template <int I0, int I1>
  __device__ __forceinline__ void part(float (&d)[4 * NG], float& r0, float& r1, float alpha = ALPHA) {
#pragma unroll
    for (int i = I0; i < I1; i++) {
      if (i + QD < NG) q[(i + QD) % (QD + 1)] = lds128f(ep + (i + QD) * 64);
      const float4 v = q[i % (QD + 1)];
#pragma unroll
      for (int e = 0; e < 4; e++) asm volatile("" : "+f"(d[4 * i + e]));
      const float al = i < I0 + QD ? alpha : ALPHA;
      r0 = gelu_acc(d[4 * i + 0], v.x, v.z, r0, al);
      r0 = gelu_acc(d[4 * i + 1], v.y, v.w, r0, al);
      r1 = gelu_acc(d[4 * i + 2], v.x, v.z, r1, al);
      r1 = gelu_acc(d[4 * i + 3], v.y, v.w, r1, al);
    }
    asm volatile("" : "+f"(r0), "+f"(r1));
  }
};
__device__ __forceinline__ float quad_sum(float r0, float r1, float r2, float r3, int lane) {
  const bool b0 = lane & 1, b1 = lane & 2;
  const float a = (b0 ? r1 : r0) + __shfl_xor_sync(0xffffffffu, b0 ? r0 : r1, 1);
  const float b = (b0 ? r3 : r2) + __shfl_xor_sync(0xffffffffu, b0 ? r2 : r3, 1);
  return (b1 ? b : a) + __shfl_xor_sync(0xffffffffu, b1 ? a : b, 2);
}
__device__ __forceinline__ void sts128f(uint32_t addr, float a, float b, float c, float d) {
  asm volatile("st.shared.v4.f32 [%0], {%1, %2, %3, %4};" ::"r"(addr), "f"(a), "f"(b), "f"(c), "f"(d) : "memory");
}
__device__ __forceinline__ void pin(float a, float b, uint32_t addr, uint32_t zero) {
  asm volatile("{\n.reg .pred p;\nsetp.ne.u32 p, %3, 0;\n@p st.shared.v2.f32 [%0], {%1, %2};\n}" ::"r"(addr), "f"(a), "f"(b), "r"(zero) : "memory");
}
__device__ __forceinline__ void hand_on(float (&d)[96], const float (&s)[96]) {
#pragma unroll
  for (int i = 0; i < 96; i++) asm volatile("mov.b32 %0, %1;" : "=f"(d[i]) : "f"(s[i]));
}
__device__ __forceinline__ uint64_t desc_x(int u) { return mkdesc(SMEM_BASE, 16, 1024, 1) + u * (UNIT / 16); }
__device__ __forceinline__ uint64_t desc_w(int u, int stride = 1) { return mkdesc(SMEM_BASE, stride * UNIT, 1024, 1) + u * (UNIT / 16); }
__device__ __forceinline__ void tile_step(float (&d)[96], uint64_t dA, uint64_t dB) {
  wg_fence();
#pragma unroll
  for (int k = 0; k < 4; k++) wgmma_ss_n192(d, dA + 2 * k, dB + 128 * k, 1);
  wg_commit();
}
template <int K0 = 0, int K1 = 4>
__device__ __forceinline__ void wide_step(float (&d)[96], float (&e)[32], uint64_t dA, uint64_t dB) {
  wg_fence();
#pragma unroll
  for (int k = K0; k < K1; k++) wgmma_ss_n256(d, e, dA + 2 * k, dB + 128 * k, 1);
  wg_commit();
}
__device__ __forceinline__ int cin_row(int c, int j) {
  if (c >= NGEMM) {
    const int e = (c - NGEMM) * NC_EXTRA + j;
    c = e < 256 ? e >> 1 : NBIG + e - 256;
    j = e < 256 ? 30 + (e & 1) : 29;
  }
  return (c >> 3) * 256 + (c & 2) * 64 + (c & 1) * 64 + (c & 4) * 8 + j;
}
__device__ __forceinline__ int cin_count(int c) {
  return c < NGEMM ? NC_GEMM + (c < NBIG) : NC_EXTRA;
}

__device__ __forceinline__ int fold_i0(int e) { return e < 2 ? 7 * e : 2 + 6 * e; }
__device__ __forceinline__ uint32_t ldg16(const void* p) { uint16_t v; asm volatile("ld.global.nc.u16 %0, [%1];" : "=h"(v) : "l"(p)); return v; }
__device__ __forceinline__ uint4 ldg128(const void* p) {
  uint4 v; asm volatile("ld.global.nc.v4.u32 {%0,%1,%2,%3}, [%4];" : "=r"(v.x), "=r"(v.y), "=r"(v.z), "=r"(v.w) : "l"(p)); return v;
}
__device__ __forceinline__ void sts64f(uint32_t addr, float a, float b) { asm volatile("st.shared.v2.f32 [%0], {%1, %2};" ::"r"(addr), "f"(a), "f"(b) : "memory"); }
__device__ __forceinline__ float to_tf32(float v) { uint32_t r; asm("cvt.rna.tf32.f32 %0, %1;" : "=r"(r) : "f"(v)); return __uint_as_float(r); }
__device__ __forceinline__ uint4 fold_chunk(uint32_t base, const uint4 t0, const uint4 t1) {
  const uint32_t t[8] = {t0.x, t0.y, t0.z, t0.w, t1.x, t1.y, t1.z, t1.w};
  uint32_t v[4];
#pragma unroll
  for (int c = 0; c < 4; c++) {
    const float w0 = __int_as_float(lds32(base + (t[2 * c] & 0xffff))) + __int_as_float(lds32(base + (t[2 * c] >> 16)));
    const float w1 = __int_as_float(lds32(base + (t[2 * c + 1] & 0xffff))) + __int_as_float(lds32(base + (t[2 * c + 1] >> 16)));
    __nv_bfloat162 pk = __floats2bfloat162_rn(w0, w1);
    v[c] = *reinterpret_cast<uint32_t*>(&pk);
  }
  return make_uint4(v[0], v[1], v[2], v[3]);
}
__device__ __forceinline__ int cw_chunk(int u, int n) {
  return ((u < 44 ? (u >> 1) * 1792 : CW_MAIN + ((u - 44) >> 1) * 1024) + (n >> 3) * 256 + (u & 1) * 128 + (n & 7) * 16) >> 4;
}
__device__ __forceinline__ void fold_weights(uint8_t* smem, uint32_t sb, int e, const __nv_bfloat16* __restrict__ wco, const GPtr gp) {
  const int tid = threadIdx.x, lane = tid & 31, warp = tid >> 5;
  const uint32_t bars = sb + OFF_BAR;
  const int i0 = fold_i0(e), i = i0 + warp;
  const bool own = i < fold_i0(e + 1);
  const uint32_t wb16 = ldg16(wco + (lane < NF ? 26 + lane : 0)), wc16 = ldg16(wco + (lane < NF ? 52 + lane : 0));
  const uint32_t w116 = ldg16(wco + (own ? i : 0));
  const uint4* tab = gp.tab;
  const uint4 ta0 = ldg128(tab + 2 * lane), ta1 = ldg128(tab + 2 * lane + 1);
  const uint4 tb0 = ldg128(tab + 64 + 2 * (lane & 15)), tb1 = ldg128(tab + 65 + 2 * (lane & 15));
  asm volatile("barrier.cluster.arrive.relaxed.aligned;\nbarrier.cluster.wait.acquire.aligned;" ::: "memory");
  if (warp >= 6) {
    for (int t = tid - 192; t < 6 * 20; t += 64) sts64f(sb + XOFF_M + 26 * 160 + t * 8, 0.f, 0.f);
    if (warp == 6 && lane < NF) {
      sts64f(sb + XOFF_M + lane * 160 + 104, bf_lo(wb16), 0.f);
      sts64f(sb + XOFF_M + lane * 160 + 112, 0.f, 0.f);
      sts64f(sb + XOFF_M + lane * 160 + 120, 0.f, 0.f);
    }
    if (warp == 7) {
      gp.s->cw[cw_chunk(lane, 28 + e)] = make_uint4(0, 0, 0, 0);
      if (lane < 16) gp.s->cw[cw_chunk(32 + lane, 28 + e)] = make_uint4(0, 0, 0, 0);
    }
  } else {
    mbar_wait(bars + 8 * BAR_GIDX, 0);
    float m0 = 0.f, m1 = 0.f, m2 = 0.f, m3 = 0.f;
    const uint32_t a = sb + XOFF_W3 + (tid < 169 ? tid : 0) * 8;
#pragma unroll 2
    for (int g = 0; g < NF; g++) {
      const int2 v = lds64(a + g * 1352);
      const float w = __shfl_sync(0xffffffffu, bf_lo(wc16), g);
      m0 = fmaf(w, bf_lo(v.x), m0); m1 = fmaf(w, bf_hi(v.x), m1);
      m2 = fmaf(w, bf_lo(v.y), m2); m3 = fmaf(w, bf_hi(v.y), m3);
    }
    if (tid < 169) {
      const int o = tid * 2, o2 = o + 1;
      sts64f(sb + XOFF_M + (o / 13) * 160 + (o % 13) * 8, to_tf32(m0), to_tf32(m1));
      sts64f(sb + XOFF_M + (o2 / 13) * 160 + (o2 % 13) * 8, to_tf32(m2), to_tf32(m3));
    }
  }
  const uint32_t sT = sb + XOFF_S + warp * 2 * 3136, sA = sT + 3136;
  const int g = lane >> 2, c = lane & 3;
  uint32_t af[2][8];
  mbar_wait(bars + 8 * BAR_FULL, 0);
  if (own) {
#pragma unroll
    for (int k = 0; k < 8; k++) {
      const int h = 4 * k + c;
      const uint32_t a = sb + XOFF_W2 + ((h < NF ? h : 0) * 676 + i * 26 + 2 * g) * 2;
      af[0][k] = lds32(a);
      af[1][k] = lds32(a + (g < 5 ? 32 : 0));
    }
#pragma unroll 1
    for (int o = lane; o < 338; o += 32) {
      const uint32_t v = lds32(sb + XOFF_W1 + (i - (i0 & ~1)) * 1352 + o * 4);
      sts64f(sA + (o / 13) * 112 + (o % 13) * 8, bf_lo(v), bf_hi(v));
    }
    if (lane < 28) sts64f(sA + lane * 112 + 104, 0.f, 0.f);
    if (lane < 2) sts64f(sT + (26 + lane) * 112 + 104, lane == 0 ? bf_lo(w116) : 0.f, 0.f);
  }
  bar_sync<4, 256>();
  if (own) {
#pragma unroll 1
    for (int n = 0; n < 4; n++) {
      float d[2][4] = {};
#pragma unroll
      for (int ks = 0; ks < 4; ks++) {
        const uint32_t b0 = lds32(sb + XOFF_M + (8 * ks + c) * 160 + (8 * n + g) * 4);
        const uint32_t b1 = lds32(sb + XOFF_M + (8 * ks + c + 4) * 160 + (8 * n + g) * 4);
#pragma unroll
        for (int m = 0; m < 2; m++)
          asm volatile("mma.sync.aligned.m16n8k8.row.col.f32.tf32.tf32.f32 {%0,%1,%2,%3}, {%4,%5,%6,%7}, {%8,%9}, {%0,%1,%2,%3};"
                       : "+f"(d[m][0]), "+f"(d[m][1]), "+f"(d[m][2]), "+f"(d[m][3])
                       : "r"(af[m][2 * ks] << 16), "r"(af[m][2 * ks] & 0xffff0000u), "r"(af[m][2 * ks + 1] << 16),
                         "r"(af[m][2 * ks + 1] & 0xffff0000u), "r"(b0), "r"(b1));
      }
      if (n < 3 || c < 2) {
        const uint32_t a = sT + 2 * g * 112 + (8 * n + 2 * c) * 4;
        sts64f(a, d[0][0], d[0][1]);
        sts64f(a + 112, d[0][2], d[0][3]);
        if (g < 5) {
          sts64f(a + 16 * 112, d[1][0], d[1][1]);
          sts64f(a + 17 * 112, d[1][2], d[1][3]);
        }
      }
    }
    __syncwarp();
    const int nt = i < 24 ? i : 2 * i - 24, na = i < 24 ? 32 + i : 2 * i - 23;
#pragma unroll 1
    for (int k = 0; k < 3; k++) {
      const bool isa = k == 1 || (k == 2 && lane >= 16);
      const uint4 v = fold_chunk(isa ? sA : sT, k < 2 ? ta0 : tb0, k < 2 ? ta1 : tb1);
      if (k < 2 || lane < 28 || na < 32) gp.s->cw[cw_chunk(k < 2 ? lane : 32 + (lane & 15), isa ? na : nt)] = v;
    }
  }
  __syncwarp();
  if (lane == 0) flag_add(&gp.s->foldflag);
  bar_sync<4, 256>();
  mbar_wait(bars + 8 * BAR_GDONE, 0);
  if (tid >= 128 && tid < 132) mbar_arrive(ev_bar(bars, EV_END));
}

__global__ void __cluster_dims__(2, 1, 1) __launch_bounds__(384, 1)
xdeepfm_kernel(const int* __restrict__ idx, const __nv_bfloat16* __restrict__ table, const __nv_bfloat16* __restrict__ w1,
               const __nv_bfloat16* __restrict__ b1, const __nv_bfloat16* __restrict__ w2,
               const __nv_bfloat16* __restrict__ ws, const __nv_bfloat16* __restrict__ wco,
               const __nv_bfloat16* __restrict__ bout, __nv_bfloat16* __restrict__ out, const GPtr gp,
               const __grid_constant__ CUtensorMap tmW, const __grid_constant__ CUtensorMap tmT,
               const __grid_constant__ CUtensorMap tmS, const __grid_constant__ CUtensorMap tmC) {
  int myidx, idx1, idx2 = 0, idx3 = 0;
  {
    const int t = threadIdx.x, b = blockIdx.x, half = (b >> 1) ^ (t >= 256 ? t >> 4 : 0);
    const int* ip = idx + (((b >> 3) & 15) * 256 + (half & 1) * 128 + (t < 256 ? t >> 1 : (b & 1) * 64 + ((t >> 1) & 48) + (t & 15))) * NF;
    asm volatile("{\n.reg .pred p;\nsetp.ge.u32 p, %5, 256;\nld.global.nc.v2.s32 {%0, %1}, [%4];\n@p ld.global.nc.v2.s32 {%2, %3}, [%4 + 8];\n}"
                 : "=r"(myidx), "=r"(idx1), "+r"(idx2), "+r"(idx3) : "l"(ip), "r"(t));
  }
  extern __shared__ __align__(1024) uint8_t smem[];
  const uint32_t sb = (uint32_t)__cvta_generic_to_shared(smem);
  const uint32_t bars = sb + OFF_BAR;
  const int tid = threadIdx.x, lane = tid & 31;
  const int warp = __shfl_sync(0xffffffffu, tid >> 5, 0);
  const int cta = blockIdx.x;
  const bool gemm = cta < NGEMM;
  const int nt = cta & 7, rank = cta & 1;

  if (warp == 8 && elect1()) {
    mbar_init(bars + 8 * BAR_GIDX, 1);
    mbar_init(bars + 8 * BAR_FULL, 1);
    mbar_init(bars + 8 * BAR_W0, 1);
    asm volatile("fence.mbarrier_init.release.cluster;" ::: "memory");
    if (gemm) {
      mbar_expect_tx(bars + 8 * BAR_W0, 4 * UNIT);
#pragma unroll
      for (int i = 0; i < 4; i++)
        tma_load(sb + (U_W + i) * UNIT, &tmW, i < 3 ? nt * 192 + i * 64 : 1536 + (nt >> 2) * 64, 0, bars + 8 * BAR_W0);
    } else {
      mbar_expect_tx(bars + 8 * BAR_GIDX, 35152);
      bulk_load(sb + XOFF_W3, ws + 2 * 17576, 35152, bars + 8 * BAR_GIDX);
    }
  }
  if (threadIdx.x < 256) {}
  else if (threadIdx.x >= 384 - 16) {
    const int l = threadIdx.x & 7;
    if (l < 7) asm volatile("prefetch.global.L2 [%0];" ::"l"(w1 + (((cta >> 3 & 15) * 2 + (cta & 1)) * 2 + ((threadIdx.x >> 3) & 1)) * DIN + (l < 6 ? (cta & 6) * 192 + l * 64 : 1536 + (cta & 4) * 16)));
  }
  else if (threadIdx.x >= 352 && threadIdx.x < 359) {
    const int l = blockIdx.x * 7 + threadIdx.x - 352;
    if (l < 824) asm volatile("prefetch.global.L2 [%0];" ::"l"(ws + (823 - l) * 64));
  }

  if (warp >= 8) {
    const int pw = warp - 8;
    const bool lead = elect1();
    if (lead) {
      if (pw) mbar_init(bars + 8 * (pw < 3 ? BAR_FULL + pw : BAR_X0), 1);
      else mbar_init(bars + 8 * BAR_GDONE, 4);
      asm volatile("fence.mbarrier_init.release.cluster;" ::: "memory");
    }
    __syncwarp();
    asm volatile("barrier.cluster.arrive.relaxed.aligned;" ::: "memory");
    if (lead) {
      if (gemm) w_prefetch(w1, 1, cta, pw);
      if (pw == 0) {
        if (gemm) {
          mbar_expect_tx(bars + 8 * BAR_FULL, 2 * UNIT);
          asm volatile("prefetch.tensormap [%0];" ::"l"(&tmT) : "memory");
          asm volatile("prefetch.tensormap [%0];" ::"l"(&tmS) : "memory");
        } else {
          const int i0 = fold_i0(cta - NGEMM) & ~1, ni = NF - i0 < 8 ? NF - i0 : 8;
          mbar_expect_tx(bars + 8 * BAR_FULL, 35152 + ni * 1352);
          bulk_load(sb + XOFF_W1, ws + i0 * 676, ni * 1352, bars + 8 * BAR_FULL);
          bulk_load(sb + XOFF_W2, ws + 17576, 35152, bars + 8 * BAR_FULL);
        }
      }
    }
    __syncwarp();
    asm volatile("setmaxnreg.dec.sync.aligned.u32 24;");
    if (elect1()) {
      mbar_init(bars + 8 * (BAR_EV + pw), 4);
      mbar_init(bars + 8 * (BAR_EV + 4 + pw), 4);
      mbar_init(bars + 8 * (BAR_FULL + 4 + pw), 1);
      if (pw < 3) mbar_init(bars + 8 * (pw == 2 ? BAR_CW : BAR_DNN + pw), pw == 0 && !gemm ? 4 : 1 + (pw & 1));
      if (pw < 2) mbar_init(bars + 8 * (pw ? BAR_PARK : BAR_FULL + 3), 1 + 7 * pw);
#pragma unroll
      for (int i = 0; i < 4; i++) mbar_init(bars + 8 * (BAR_CFULL + pw * 4 + i), 1);
      if (pw < 2) mbar_init(bars + 8 * (BAR_C0 + pw), 1);
      asm volatile("fence.mbarrier_init.release.cluster;" ::: "memory");
    }
    __syncwarp();
    bar_sync<6, 128>();
    asm volatile("barrier.cluster.wait.acquire.aligned;" ::: "memory");
    if (gemm) {
      {
        const uint32_t a = sb + OFF_GIDX + ((lane >> 4) * 64 + pw * 16 + (lane & 15)) * NF * 4;
        asm volatile("st.shared.v2.b32 [%0], {%1, %2};\nst.shared.v2.b32 [%0 + 8], {%3, %4};"
                     ::"r"(a), "r"(myidx), "r"(idx1), "r"(idx2), "r"(idx3) : "memory");
        __syncwarp();
      }
      if (elect1()) {
#pragma unroll
        for (int j = 0; j < 16; j += 8) {
          int r[8];
#pragma unroll
          for (int i = 0; i < 8; i++) r[i] = lds32(sb + OFF_GIDX + ((64 + pw * 16 + j + i) * NF) * 4);
#pragma unroll
          for (int i = 0; i < 8; i++) tma_row_mc(sb + U_XB * UNIT + (rank * 64 + pw * 16 + j + i) * 128, &tmT, r[i], bars + 8 * BAR_FULL);
        }
        int s = 1;
#pragma unroll 1
        for (int fi = 1; fi < NF; fi++) {
          const int f = fresh(fi), pw = fresh(warp) - 8, ct = fresh(cta), nt = ct & 7;
          const int t = f - FS, st = t < 0 ? s : (t & 3) ^ ((t >> 1) & 1), e = f - 3 - (t > 1);
          const uint32_t fb = bars + 8 * (BAR_FULL + (f & 7)), ia = sb + OFF_GIDX + (pw * 16 * NF + f) * 4;
          const uint32_t d = sb + (st == 3 ? U_SP : 2 * st) * UNIT + ((ct & 1) * 64 + pw * 16) * 128;
          if (f == 4) mbar_wait(bars + 8 * BAR_GIDX, 0);
          int r[2][RB];
#pragma unroll
          for (int i = 0; i < RB; i++) r[0][i] = lds32(ia + i * NF * 4);
          if (e >= 0) mbar_wait(ev_bar(bars, e), ev_par(e));
          if (pw == 0) mbar_expect_tx(fb, t < 0 ? 8 * UNIT : 6 * UNIT);
#pragma unroll
          for (int j = 0; j < 16 / RB; j++) {
#pragma unroll
            for (int i = 0; i < RB; i++) r[(j + 1) & 1][i] = lds32(ia + (RB * j + RB + i + (RB * j + RB >= 16) * 48) * NF * 4);
#pragma unroll
            for (int i = 0; i < RB; i++) tma_row_mc(d + (RB * j + i) * 128, &tmT, r[j & 1][i], fb);
          }
          if (t < 0) {
#pragma unroll
            for (int j = 0; j < 16 / RB; j++) {
              if (j + 1 < 16 / RB) {
#pragma unroll
                for (int i = 0; i < RB; i++) r[(j + 1) & 1][i] = lds32(ia + (64 + RB * j + RB + i) * NF * 4);
              }
#pragma unroll
              for (int i = 0; i < RB; i++) tma_row_mc(d + U_XB * UNIT + (RB * j + i) * 128, &tmT, r[j & 1][i], fb);
            }
          }
          tma_load(sb + (U_W + 4 * st + pw) * UNIT, &tmW, pw < 3 ? nt * 192 + pw * 64 : 1536 + (nt >> 2) * 64, f * 64, fb);
          if (f == GI && pw < 2) {
            if (pw == 0) mbar_expect_tx(bars + 8 * BAR_GIDX, 128 * NF * 4);
            bulk_load(sb + OFF_GIDX + pw * 64 * NF * 4, idx + ((ct >> 3) * 256 + (((ct >> 1) ^ pw) & 1) * 128 + (ct & 1) * 64) * NF, 64 * NF * 4, bars + 8 * BAR_GIDX);
          }
          if (f == GI && pw == 2) asm volatile("prefetch.tensormap [%0];" ::"l"(&tmC) : "memory");
          if (f + WD < NF) w_prefetch(w1, f + WD, ct, pw);
          if (++s == 3) s = 0;
        }
        mbar_wait(bars + 8 * BAR_T, 0);
#pragma unroll 1
        for (int ti = 0; ti < 8; ti++) {
          const int t = fresh(ti), pw = fresh(warp) - 8, e = t < 4 ? 22 - !t : 19 + t;
          const uint32_t ia = sb + OFF_TIDX + t * 256 + pw * 64, fb = bars + 8 * (BAR_FULL + ((NF + t) & 7));
          const uint32_t d = sb + b_x(t) * UNIT + ((fresh(cta) & 1) * 64 + pw * 16) * 128;
          int4 r[2];
          r[0] = lds128(ia);
          r[1] = lds128(ia + 16);
          mbar_wait(ev_bar(bars, e), ev_par(e));
          if (pw == 0) mbar_expect_tx(fb, t < 3 ? 2 * UNIT : 5 * UNIT);
#pragma unroll
          for (int j = 0; j < 4; j++) {
            tma_row_mc(d + (4 * j + 0) * 128, &tmT, r[j & 1].x, fb);
            tma_row_mc(d + (4 * j + 1) * 128, &tmT, r[j & 1].y, fb);
            tma_row_mc(d + (4 * j + 2) * 128, &tmT, r[j & 1].z, fb);
            tma_row_mc(d + (4 * j + 3) * 128, &tmT, r[j & 1].w, fb);
            if (j < 2) r[j & 1] = lds128(ia + 32 + 16 * j);
          }
        }
        mbar_arrive(bars + 8 * BAR_GDONE);
      }
      __syncwarp();
    }
    asm volatile("setmaxnreg.inc.sync.aligned.u32 %0;" ::"n"(PREG));
    {
    int cta; asm volatile("mov.u32 %0, %%ctaid.x;" : "=r"(cta));
    int tid; asm volatile("mov.u32 %0, %%tid.x;" : "=r"(tid));
    const int lane = tid & 31, pw = __shfl_sync(0xffffffffu, tid >> 5, 0) - 8;
    const bool gemm = cta < NGEMM;
    const int bt = cta >> 3, nt = cta & 7;
    const int ncin = cin_count(cta);
    unsigned epoch;
    auto load_cw = [&]() {
      if (elect1()) {
        asm volatile("fence.proxy.async.global;" ::: "memory");
        mbar_expect_tx(bars + 8 * BAR_CW, CW_BYTES);
        bulk_load(sb + OFF_CW, gp.s->cw, CW_CUT * 1792, bars + 8 * BAR_CW);
        bulk_load(sb + OFF_CW2, gp.s->cw + CW_CUT * 1792 / 16, (22 - CW_CUT) * 1792, bars + 8 * BAR_CW);
        bulk_load(sb + OFF_CWL, gp.s->cw + CW_MAIN / 16, CW_LIN, bars + 8 * BAR_CW);
      }
    };
    if (!gemm) {
      epoch = gp.s->epoch[cta] + 1;
#pragma unroll 1
      for (int i = pw * 32 + lane; i < NC_EXTRA * 13; i += 128)
        asm volatile("cp.async.ca.shared.global [%0], [%1], 8;" ::"r"(sb + XOFF_CIDX + i * 8), "l"(idx + cin_row(cta, i / 13) * NF + i % 13 * 2) : "memory");
      if (elect1()) {
#pragma unroll 1
        for (int i = 0; i < NPAIR; i++) mbar_init(sb + XOFF_BAR + (pw * NPAIR + i) * 8, pw & 1 ? 4 : 1);
        asm volatile("fence.mbarrier_init.release.cluster;" ::: "memory");
      }
      asm volatile("cp.async.wait_all;" ::: "memory");
      bar_sync<6, 128>();
      if (elect1()) mbar_arrive(bars + 8 * BAR_GDONE);
      __syncwarp();
      if (pw == 3) {
        flag_wait(&gp.s->foldflag, epoch * NEXTRA * 8, 0);
        __syncwarp();
        load_cw();
      }
      if (elect1()) {
        const int wg = pw & 1;
#pragma unroll 1
        for (int t = pw < 2 ? -1 : 1; t < NPAIR; t += t < 0 ? 1 : 2) {
          const int j = t < 0 ? 0 : 2 * t + 1, n = t < 0 || t == NPAIR - 1 ? 1 : 2;
          const uint32_t cb = t < 0 ? bars + 8 * (BAR_C0 + wg) : sb + XOFF_BAR + (wg * 2 * NPAIR + t) * 8;
          if (t == 0 || t == 1) mbar_wait(ev_bar(bars, EV_END), ev_par(EV_END));
          if (t >= 4) mbar_wait(cb + 8 * (NPAIR - 4), 0);
          mbar_expect_tx(cb, n * NF * 128);
#pragma unroll 1
          for (int i = 0; i < n; i++) {
            const uint32_t d = sb + (t < 0 ? OFF_GIDX + wg * XSLOT : XOFF_SLOT + (wg * 8 + (t & 3) * 2 + i) * XSLOT);
            const uint32_t ia = sb + XOFF_CIDX + (wg * (NC_EXTRA / 2) + j + i) * NF * 4;
#pragma unroll
            for (int k = 0; k < NF; k += 2) {
              const int2 r = lds64(ia + k * 4);
              tma_row(d + k * 128, &tmT, r.x, cb);
              tma_row(d + (k + 1) * 128, &tmT, r.y, cb);
            }
          }
        }
      }
      __syncwarp();
    } else {
      epoch = lds32(bars + 8 * BAR_EPOCH);
      if (pw == 3) {
        mbar_wait(ev_bar(bars, EV_CW), ev_par(EV_CW));
        load_cw();
      }
      constexpr int n0 = NC_WG0;
      const uint32_t ep = sb + OFF_EPI + (lane & 3) * 16, pk = sb + (pw * 32 + lane) * 16;
      float r2 = 0.f, r3 = 0.f;
      mbar_wait(bars + 8 * BAR_GDONE, 0);
      mbar_wait(bars + 8 * BAR_X0, 0);
      asm volatile("fence.proxy.async.global;" ::: "memory");
#pragma unroll 1
      for (int k = 0; k < 5; k++) {
        const int n = pw + 4 * k, wg = n > 1 && ((n & 1) || n == 2), j = n == 1 ? 1 : n < 3 ? 0 : n - 1 - wg;
        const int m = min((wg ? ncin - n0 : n0) - j, j ? 2 : 1), r = wg * n0 + j;
        const uint32_t cb = bars + 8 * (j ? BAR_CFULL + wg * 8 + (j >> 1) : BAR_C0 + wg), d = sb + slot_of(wg, j);
        if (n >= 2 && n < 12) {
          const int e = n == 2 ? EV_CW : n < 7 ? EV_SLOT : EV_END;
          mbar_wait(ev_bar(bars, e), ev_par(e));
        }
        auto load_sample = [&](int i) {
          const int4 u = lds128(sb + OFF_CIDX + (r + i) * 32), v = lds128(sb + OFF_CIDX + (r + i) * 32 + 16);
          const uint32_t a = d + i * XSLOT;
          tma_row(a, &tmC, (cta * 32 + r + i) * FS, cb);
          tma_row(a + (FS + 0) * 128, &tmT, u.x, cb);
          tma_row(a + (FS + 1) * 128, &tmT, u.y, cb);
          tma_row(a + (FS + 2) * 128, &tmT, u.z, cb);
          tma_row(a + (FS + 3) * 128, &tmT, u.w, cb);
          tma_row(a + (FS + 4) * 128, &tmT, v.x, cb);
          tma_row(a + (FS + 5) * 128, &tmT, v.y, cb);
          tma_row(a + (FS + 6) * 128, &tmT, v.z, cb);
          tma_row(a + (FS + 7) * 128, &tmT, v.w, cb);
        };
        if (m > 0 && elect1()) {
          mbar_expect_tx(cb, m * NF * 128);
#pragma unroll 1
          for (int i = 0; i < m; i++) load_sample(i);
        }
        __syncwarp();
        if (k == 0 || k == 4) continue;
        if (k == 1) {
          mbar_wait(bars + 8 * BAR_PARK, 0);
        }
        uint32_t a = k == 3 ? OFF_PARK2 : OFF_PARK + (k - 1) * 8 * 2048, b = (k - 1) * 8 * 64;
#pragma unroll 1
        for (const uint32_t e = b + 8 * 64; b != e; a += BGN * 2048, b += BGN * 64) {
          float4 v[BGN], q[BGN];
#pragma unroll
          for (int i = 0; i < BGN; i++) { v[i] = lds128f(pk, a + i * 2048); q[i] = lds128f(ep, b + i * 64); }
#pragma unroll
          for (int i = 0; i < BGN; i++) {
            r2 = gelu_acc(v[i].x, q[i].x, q[i].z, r2);
            r3 = gelu_acc(v[i].z, q[i].x, q[i].z, r3);
            r2 = gelu_acc(v[i].y, q[i].y, q[i].w, r2);
            r3 = gelu_acc(v[i].w, q[i].y, q[i].w, r3);
          }
        }
      }
      const float4 w = lds128f(pk + OFF_RS0);
      const int2 v = lds64(sb + OFF_RS1 + (pw * 32 + lane) * 8);
      uint2* dst = gp.s->part + (nt * NB + bt * 256 + pw * 16);
      const uint32_t o = (lane & 1) * 8 + (lane & 2) * 32 + (lane >> 2);
      put_tagged(dst + (o ^ ((cta & 2) * 64 + (~cta & 1) * 64)), quad_sum(w.x, w.y, w.z, w.w, lane), epoch);
      put_tagged(dst + (o ^ ((~cta & 2) * 64)), quad_sum(__int_as_float(v.x), __int_as_float(v.y), r2, r3, lane), epoch);
    }
    if (pw == 3 || !gemm) {
      float s = (sb & 0xFFFFFF) == SMEM_BASE ? bf2f(bout[0]) : __int_as_float(0x7fc00000);
      const int r = gemm ? lane : pw * (NC_EXTRA / 4) + min(lane, NC_EXTRA / 4 - 1), row = cin_row(cta, r);
      const uint2* src = gp.s->part + row;
      uint2 v[8];
#pragma unroll 1
      for (int i = 0; i < 100000; i++) {
        unsigned miss = 0;
#pragma unroll
        for (int n = 0; n < 8; n++)
          asm volatile("ld.relaxed.gpu.global.v2.b32 {%0, %1}, [%2];" : "=r"(v[n].x), "=r"(v[n].y) : "l"(src + n * NB) : "memory");
#pragma unroll
        for (int n = 0; n < 8; n++) miss |= v[n].y ^ epoch;
        if (__all_sync(0xffffffffu, miss == 0)) break;
        __nanosleep(POLL);
      }
#pragma unroll
      for (int n = 0; n < 8; n++) s += __uint_as_float(v[n].x);
      sts64f(sb + OFF_DNN + r * 8, s, __int_as_float(row));
      __syncwarp();
      if (lane == 0) mbar_arrive(bars + 8 * BAR_DNN);
      if (pw == 3 && lane == 0) gp.s->epoch[fresh(cta)] = epoch;
    }
    }
  } else {
    const int wg = warp >> 2;
    const int p = tid & 127;
    if (gemm) {
      asm volatile("barrier.cluster.arrive.relaxed.aligned;" ::: "memory");
#pragma unroll
      for (int i = 0; i < 4; i++) {
        const int r = __shfl_sync(0xffffffffu, myidx, 8 * i + 2 * (lane >> 3));
        const int row = warp * 16 + 4 * i + (lane >> 3);
        cpasync16(sb + row * 128 + (((lane & 7) ^ (row & 7)) << 4), table + (size_t)r * 64 + (lane & 7) * 8);
      }
      asm volatile("barrier.cluster.wait.acquire.aligned;" ::: "memory");
    } else {
      fold_weights(smem, sb, cta - NGEMM, wco, gp);
    }
    asm volatile("setmaxnreg.inc.sync.aligned.u32 224;");
    float r0 = 0.f, r1 = 0.f, r2 = 0.f, r3 = 0.f;
    CinCtx c;
    float accA[28];
    uint32_t xA[10][2], z[8];
    const uint32_t ep = sb + OFF_EPI + (lane & 3) * 16;
    auto load_w = [&](int t) {
      const int w = warp & 3;
      if (w < 3 && elect1())
        tma_load(sb + (b_w(t) + b_ws(t) * w) * UNIT, &tmW, nt * 192 + w * 64, (NF - 1 - t) * 64, bars + 8 * (BAR_FULL + ((NF + t) & 7)));
    };
    auto keep_x = [&](int f, int u) {
      if (warp == 0 && elect1()) tma_store(&tmS, f * 64, cta * 32, sb + (u + rank) * UNIT + (nt >> 2) * 4096);
    };
    auto role = [&](int w) { int c; asm volatile("mov.u32 %0, %%ctaid.x;" : "=r"(c)); return c < NGEMM && wg == w; };
    if (role(0)) {
      asm volatile("setmaxnreg.inc.sync.aligned.u32 256;");
      float d0[96], dx[32], dw[96];
      Gelu<24> g0;
      mbar_wait(bars + 8 * BAR_W0, 0);
      asm volatile("cp.async.wait_all;" ::: "memory");
      asm volatile("fence.proxy.async.shared::cta;" ::: "memory");
      bar_sync<2, 256>();
      const uint64_t dA0 = desc_x(rank), dA1 = desc_x(rank ^ 1);
      wg_fence();
#pragma unroll
      for (int k = 0; k < 4; k++) {
        wgmma_ss_n256(dw, dx, dA0 + 2 * k, desc_w(U_W) + 128 * k, k != 0);
        wgmma_ss_n192(d0, dA1 + 2 * k, desc_w(U_W) + 128 * k, k != 0);
      }
      wg_commit();
      keep_x(0, 0);
#pragma unroll 1
      for (int f = 1; f < NF - 3; f++) {
        mbar_wait(bars + 8 * (BAR_FULL + (f & 7)), (f >> 3) & 1);
        const int st = (STAGES >> (2 * f)) & 3, xo = (st == 3 ? U_SP : 2 * st) * (UNIT / 16);
        const uint64_t dB = desc_w(U_W + 4 * st);
        wg_fence();
        wgmma_ss_n256(dw, dx, dA0 + xo, dB, 1);
        wgmma_ss_n192(d0, dA1 + xo, dB, 1);
        wg_commit();
        store_read<0>();
        wg_wait<1>();
        if (p < (f > FS ? 4 : 2)) mbar_arrive_cta(ev_bar(bars, f - 1), p & 1);
#pragma unroll
        for (int k = 1; k < 4; k++) {
          wgmma_ss_n256(dw, dx, dA0 + xo + 2 * k, dB + 128 * k, 1);
          wgmma_ss_n192(d0, dA1 + xo + 2 * k, dB + 128 * k, 1);
        }
        wg_commit();
        if (f < FS) keep_x(f, 2 * st);
      }
      {
        constexpr int x3 = 2 * (UNIT / 16), x4 = U_SP * (UNIT / 16), x5 = 4 * (UNIT / 16);
        const uint64_t dB3 = desc_w(U_W + 4), dB4 = desc_w(U_W + 12), dB5 = desc_w(U_W + 8);
        mbar_wait(bars + 8 * (BAR_FULL + 7), 0);
        tile_step(d0, dA1 + x3, dB3);
        wg_wait<1>();
        if (p < 4) mbar_arrive_cta(ev_bar(bars, NF - 4), p & 1);
        mbar_wait(bars + 8 * (BAR_FULL + 0), 1);
        tile_step(d0, dA1 + x4, dB4);
        mbar_wait(bars + 8 * (BAR_FULL + 1), 1);
        tile_step(d0, dA1 + x5, dB5);
        wide_step(dw, dx, dA0 + x3, dB3);
        g0.start(ep);
        wg_wait<1>();
        wide_step(dw, dx, dA0 + x4, dB4);
        g0.part<0, PE1>(d0, r0, r1, bars + 8 * BAR_W0);
        pin(r0, r1, ep, gp.zero);
        wg_wait<1>();
        if (p < 4) mbar_arrive_cta(ev_bar(bars, NF - 3), p & 1);
        wide_step<0, HK>(dw, dx, dA0 + x5, dB5);
        g0.part<PE1, PE2>(d0, r0, r1, bars + 8 * BAR_W0);
        pin(r0, r1, ep, gp.zero);
        wg_wait<1>();
        bar_arrive<4, 256>();
        if (p < 4) mbar_arrive_cta(ev_bar(bars, NF - 2), p & 1);
        wide_step<HK, 4>(dw, dx, dA0 + x5, dB5);
        g0.part<PE2, PE0>(d0, r0, r1);
        pin(r0, r1, ep, gp.zero);
        wg_wait<0>();
        load_w(3);
        if (p < 4) mbar_arrive_cta(ev_bar(bars, NF - 1), p & 1);
        asm volatile("cp.async.bulk.wait_group 0;" ::: "memory");
        if (warp == 0 && elect1()) mbar_arrive(bars + 8 * BAR_X0);
      }
      g0.part<PE0, 24>(d0, r0, r1);
      Gelu<8> gx;
      gx.start(ep + 24 * 64);
      gx.part<0, 8>(dx, r2, r3);
      float d1[96];
      hand_on(d1, dw);
      asm volatile("setmaxnreg.dec.sync.aligned.u32 224;");
      Gelu<24> g1;
      g1.start(ep);
      g1.part<0, 24>(d1, r2, r3);
    }
    if (role(1)) {
      float d0[96], dw[96];
      asm volatile("cp.async.wait_all;" ::: "memory");
      asm volatile("fence.proxy.async.shared::cta;" ::: "memory");
      bar_arrive<2, 256>();
      {
        const int col = p < 96 ? nt * 96 + p : 768 + (nt >> 2) * 32 + (p - 96);
        const uint32_t bb = __ldg(reinterpret_cast<const uint32_t*>(b1) + col), ww = __ldg(reinterpret_cast<const uint32_t*>(w2) + col);
        reinterpret_cast<float4*>(smem + OFF_EPI)[p] =
            make_float4(ALPHA * bf_lo(bb), ALPHA * bf_hi(bb), (0.5f / ALPHA) * bf_lo(ww), (0.5f / ALPHA) * bf_hi(ww));
      }
      mbar_wait(bars + 8 * BAR_W0, 0);
      mbar_wait(bars + 8 * BAR_FULL, 0);
      wg_fence();
#pragma unroll
      for (int k = 0; k < 4; k++) {
        wgmma_ss_n192(d0, desc_x(U_XB) + 2 * k, desc_w(U_W) + 128 * k, k != 0);
        wgmma_ss_n192(dw, desc_x(U_XB + 1) + 2 * k, desc_w(U_W) + 128 * k, k != 0);
      }
      wg_commit();
      int s = 1;
#pragma unroll 1
      for (int f = 1; f < FS; f++) {
        mbar_wait(bars + 8 * (BAR_FULL + (f & 7)), (f >> 3) & 1);
        const uint64_t dA = desc_x(U_XB + 2 * s), dB = desc_w(U_W + 4 * s);
        wg_fence();
        wgmma_ss_n192(d0, dA, dB, 1);
        wgmma_ss_n192(dw, dA + 512, dB, 1);
        wg_commit();
        wg_wait<1>();
        if (p < 2) mbar_arrive_cta(ev_bar(bars, f - 1), p);
#pragma unroll
        for (int k = 1; k < 4; k++) {
          wgmma_ss_n192(d0, dA + 2 * k, dB + 128 * k, 1);
          wgmma_ss_n192(dw, dA + 512 + 2 * k, dB + 128 * k, 1);
        }
        wg_commit();
        if (++s == 3) s = 0;
      }
      wg_wait<0>();
      if (p < 2) mbar_arrive_cta(ev_bar(bars, FS - 1), p);
      {
        const uint32_t a = sb + OFF_GIDX + 64 * NF * 4;
        int v[4];
#pragma unroll
        for (int i = 0; i < 4; i++) v[i] = lds32(a + (((p & 15) * 4 + i) * NF + (NF - 1 - (p >> 4))) * 4);
        const int2 w = lds64(sb + OFF_GIDX + (((nt >> 2) * 32 + (p >> 2)) * NF + FS + (p & 3) * 2) * 4);
        asm volatile("st.shared.v2.b32 [%0], {%1, %2};" ::"r"(sb + OFF_CIDX + p * 8), "r"(w.x), "r"(w.y) : "memory");
        bar_sync<3, 128>();
        asm volatile("st.shared.v4.b32 [%0], {%1, %2, %3, %4};" ::"r"(sb + OFF_TIDX + p * 16), "r"(v[0]), "r"(v[1]), "r"(v[2]), "r"(v[3]) : "memory");
        bar_sync<3, 128>();
        if (p < 2) {
          const unsigned epoch = gp.s->epoch[cta] + 1;
          flag_wait(&gp.s->foldflag, epoch * NEXTRA * 8, 0);
          sts32f(bars + 8 * BAR_EPOCH, __uint_as_float(epoch));
          mbar_arrive(bars + 8 * BAR_T);
        }
        __syncwarp();
      }
      mbar_wait(ev_bar(bars, FS), ev_par(FS));
      mbar_wait(bars + 8 * (BAR_FULL + 2), 1);
      bar_sync<4, 256>();
#pragma unroll
      for (int t = 0; t < 4; t++) {
        if (t) mbar_wait(bars + 8 * (BAR_FULL + 2 + t), 1);
        const uint64_t dA = desc_x(b_x(t)), dB = desc_w(b_w(t), b_ws(t));
        wg_fence();
#pragma unroll
        for (int k = 0; k < 4; k++) {
          wgmma_ss_n192(d0, dA + 2 * k, dB + 128 * k, 1);
          wgmma_ss_n192(dw, dA + 512 + 2 * k, dB + 128 * k, 1);
          if (k == 1 && t) {
            wg_commit();
            wg_wait<1>();
            wg_fence();
          }
        }
        wg_commit();
        if (t) {
          if (t == 1) mbar_wait(ev_bar(bars, NF - 1), ev_par(NF - 1));
          load_w(3 + t);
          if (t == 1 && p < 4) mbar_arrive_cta(ev_bar(bars, 26), p & 1);
        }
      }
      mbar_wait(bars + 8 * (BAR_FULL + 6), 1);
      tile_step(d0, desc_x(b_x(4)), desc_w(b_w(4)));
      wg_wait<1>();
      load_w(7);
      if (p < 4) mbar_arrive(ev_bar(bars, EV_CW));
      mbar_wait(bars + 8 * (BAR_FULL + 7), 1);
      tile_step(d0, desc_x(b_x(5)), desc_w(b_w(5)));
      mbar_wait(bars + 8 * (BAR_FULL + 0), 0);
      tile_step(d0, desc_x(b_x(6)), desc_w(b_w(6)));
      mbar_wait(bars + 8 * (BAR_FULL + 1), 0);
      tile_step(d0, desc_x(b_x(7)), desc_w(b_w(7), 4));
      tile_step(dw, desc_x(b_x(4) + 1), desc_w(b_w(4)));
      Gelu<24> g0;
      g0.start(ep);
      wg_wait<1>();
      tile_step(dw, desc_x(b_x(5) + 1), desc_w(b_w(5)));
      g0.part<0, PS>(d0, r0, r1);
      pin(r0, r1, ep, gp.zero);
      wg_wait<1>();
      if (p < 4) mbar_arrive(ev_bar(bars, 30));
      tile_step(dw, desc_x(b_x(6) + 1), desc_w(b_w(6)));
      g0.part<PS, PS + PS2>(d0, r0, r1);
      pin(r0, r1, ep, gp.zero);
      wg_wait<1>();
      tile_step(dw, desc_x(b_x(7) + 1), desc_w(b_w(7), 4));
      g0.part<PS + PS2, 24>(d0, r0, r1);
      sts64f(sb + OFF_RS1 + p * 8, r0, r1);
      cin_begin(c, sb, 1, slot_of(1, 0), xA, accA, z);
      if (p < 4) mbar_arrive(ev_bar(bars, EV_END));
#pragma unroll
      for (int i = 0; i < 24; i++)
        sts128f(sb + p * 16 + (i < 16 ? OFF_PARK + i * 2048 : OFF_PARK2 + (i - 16) * 2048), dw[4 * i], dw[4 * i + 1], dw[4 * i + 2], dw[4 * i + 3]);
      __syncwarp();
      if (lane == 0) mbar_arrive(bars + 8 * BAR_PARK);
    }
    if (!role(1)) {
      cin_begin(c, sb, wg, OFF_GIDX + wg * XSLOT, xA, accA, z);
      sts128f(sb + OFF_RS0 + p * 16, r0, r1, r2, r3);
      __syncwarp();
      if (lane == 0) mbar_arrive(bars + 8 * BAR_PARK);
    }

    {
    int cta, tid;
    asm volatile("mov.u32 %0, %%ctaid.x;" : "=r"(cta));
    asm volatile("mov.u32 %0, %%tid.x;" : "=r"(tid));
    cta = __shfl_sync(0xffffffffu, cta, 0);
    const bool gemm = cta < NGEMM;
    const int p = tid & 127, wg = __shfl_sync(0xffffffffu, tid >> 7, 0);
    const int ncin = cin_count(cta);
    const int n0 = gemm ? NC_WG0 : NC_EXTRA / 2;
    const int rb = wg ? n0 : 0;
    const int nj = wg ? ncin - n0 : n0;
    cin_setup(c, sb, wg, p, gemm, nj, gp.zero);
    uint32_t fa = sb + (gemm ? slot_of(wg, (p >> 3) + 1) + NF * 128 : (wg ? XOFF_CIN1 : XOFF_CIN0) + (p >> 3) * CROW) + (p & 7) * 16, fd = sb + OFF_DNN + rb * 8;
    asm volatile("" : "+r"(fa), "+r"(fd));
    auto wg_sync = [&]() { if (wg == 0) bar_sync<1, 128>(); else bar_sync<3, 128>(); };
    auto result = [&](int r, bool on) {
      const uint32_t a = fa + (r & ~15) * CROW;
      const float4 v0 = lds128f(a), v1 = lds128f(a + 128), v2 = lds128f(a + 256), v3 = lds128f(a + 384);
      const int2 dn = lds64(fd + r * 8);
      float s = (((v0.x + v0.y) + (v0.z + v0.w)) + ((v1.x + v1.y) + (v1.z + v1.w))) +
                (((v2.x + v2.y) + (v2.z + v2.w)) + ((v3.x + v3.y) + (v3.z + v3.w)));
      s += __shfl_xor_sync(0xffffffffu, s, 1);
      s += __shfl_xor_sync(0xffffffffu, s, 2);
      s += __shfl_xor_sync(0xffffffffu, s, 4);
      if ((p & 7) == 0 && on) out[dn.y] = __float2bfloat16(s + __int_as_float(dn.x));
    };
    mbar_wait(gemm ? bars + 8 * BAR_GDONE : ev_bar(bars, EV_END), 0);
    cin_run(c, nj, xA, accA, z, [&]() {
      mbar_wait(bars + 8 * BAR_DNN, 0);
    }, [&](int j) {
    });
    wg_sync();
#pragma unroll 1
    for (int r = p >> 3; r < ((nj + 15) & ~15); r += 16) result(r, r < nj);
    }
  }
}

typedef CUresult (*EncodeFn)(CUtensorMap*, CUtensorMapDataType, cuuint32_t, void*, const cuuint64_t*, const cuuint64_t*,
                             const cuuint32_t*, const cuuint32_t*, CUtensorMapInterleave, CUtensorMapSwizzle,
                             CUtensorMapL2promotion, CUtensorMapFloatOOBfill);

extern "C" void kernel_launch(void* const* d_in, const int* in_sizes, int n_in, void* d_out, int out_size) {
  void* fn = nullptr;
  cudaDriverEntryPointQueryResult q;
  cudaGetDriverEntryPoint("cuTensorMapEncodeTiled", &fn, cudaEnableDefault, &q);
  EncodeFn enc = (EncodeFn)fn;
  CUtensorMap tmW, tmT, tmS, tmC;
  const cuuint32_t es[3] = {1, 1, 1};
  {
    cuuint64_t dims[2] = {DIN, DIN}, st[1] = {DIN * 2};
    cuuint32_t box[2] = {64, 64};
    enc(&tmW, CU_TENSOR_MAP_DATA_TYPE_BFLOAT16, 2, d_in[4], dims, st, box, es, CU_TENSOR_MAP_INTERLEAVE_NONE,
        CU_TENSOR_MAP_SWIZZLE_128B, CU_TENSOR_MAP_L2_PROMOTION_NONE, CU_TENSOR_MAP_FLOAT_OOB_FILL_NONE);
  }
  {
    cuuint64_t dims[2] = {64, (cuuint64_t)(in_sizes[1] / 64)}, st[1] = {128};
    cuuint32_t box[2] = {64, 1};
    enc(&tmT, CU_TENSOR_MAP_DATA_TYPE_BFLOAT16, 2, d_in[1], dims, st, box, es, CU_TENSOR_MAP_INTERLEAVE_NONE,
        CU_TENSOR_MAP_SWIZZLE_128B, CU_TENSOR_MAP_L2_PROMOTION_NONE, CU_TENSOR_MAP_FLOAT_OOB_FILL_NONE);
  }
  void* x0 = nullptr;
  cudaGetSymbolAddress(&x0, g_x0);
  {
    cuuint64_t dims[2] = {FS * 64, NB}, st[1] = {FS * 128};
    cuuint32_t box[2] = {64, NC_GEMM + 1};
    enc(&tmS, CU_TENSOR_MAP_DATA_TYPE_BFLOAT16, 2, x0, dims, st, box, es, CU_TENSOR_MAP_INTERLEAVE_NONE,
        CU_TENSOR_MAP_SWIZZLE_128B, CU_TENSOR_MAP_L2_PROMOTION_NONE, CU_TENSOR_MAP_FLOAT_OOB_FILL_NONE);
  }
  {
    cuuint64_t dims[2] = {64, NB * FS}, st[1] = {128};
    cuuint32_t box[2] = {64, FS};
    enc(&tmC, CU_TENSOR_MAP_DATA_TYPE_BFLOAT16, 2, x0, dims, st, box, es, CU_TENSOR_MAP_INTERLEAVE_NONE,
        CU_TENSOR_MAP_SWIZZLE_128B, CU_TENSOR_MAP_L2_PROMOTION_NONE, CU_TENSOR_MAP_FLOAT_OOB_FILL_NONE);
  }
  GPtr gp;
  gp.zero = 0;
  cudaGetSymbolAddress((void**)&gp.s, g_scratch);
  cudaGetSymbolAddress((void**)&gp.tab, g_slot_tab);
  cudaFuncSetAttribute(xdeepfm_kernel, cudaFuncAttributeMaxDynamicSharedMemorySize, SMEM_BYTES);
  xdeepfm_kernel<<<GRID, 384, SMEM_BYTES, cudaStreamPerThread>>>(
      (const int*)d_in[0], (const __nv_bfloat16*)d_in[1], (const __nv_bfloat16*)d_in[4], (const __nv_bfloat16*)d_in[5],
      (const __nv_bfloat16*)d_in[6], (const __nv_bfloat16*)d_in[2], (const __nv_bfloat16*)d_in[3],
      (const __nv_bfloat16*)d_in[7], (__nv_bfloat16*)d_out, gp, tmW, tmT, tmS, tmC);
}
```

```cpp
#include <cuda_runtime.h>
#include <cuda_bf16.h>
#include <cuda.h>
#include <stdint.h>

__device__ __forceinline__ void wgmma_ss_n256(float (&d)[96], float (&e)[32], uint64_t descA, uint64_t descB, int scaleD) {
  asm volatile("{\n.reg .pred p;\nsetp.ne.b32 p, %130, 0;\n"
      "wgmma.mma_async.sync.aligned.m64n256k16.f32.bf16.bf16 {"
      "%0, %1, %2, %3, %4, %5, %6, %7, %8, %9, %10, %11, %12, %13, %14, %15,"
      "%16, %17, %18, %19, %20, %21, %22, %23, %24, %25, %26, %27, %28, %29, %30, %31,"
      "%32, %33, %34, %35, %36, %37, %38, %39, %40, %41, %42, %43, %44, %45, %46, %47,"
      "%48, %49, %50, %51, %52, %53, %54, %55, %56, %57, %58, %59, %60, %61, %62, %63,"
      "%64, %65, %66, %67, %68, %69, %70, %71, %72, %73, %74, %75, %76, %77, %78, %79,"
      "%80, %81, %82, %83, %84, %85, %86, %87, %88, %89, %90, %91, %92, %93, %94, %95,"
      "%96, %97, %98, %99, %100, %101, %102, %103, %104, %105, %106, %107, %108, %109, %110, %111,"
      "%112, %113, %114, %115, %116, %117, %118, %119, %120, %121, %122, %123, %124, %125, %126, %127"
      "}, %128, %129, p, 1, 1, 0, 1;\n}\n"
      : "+f"(d[0]), "+f"(d[1]), "+f"(d[2]), "+f"(d[3]), "+f"(d[4]), "+f"(d[5]), "+f"(d[6]), "+f"(d[7]),
        "+f"(d[8]), "+f"(d[9]), "+f"(d[10]), "+f"(d[11]), "+f"(d[12]), "+f"(d[13]), "+f"(d[14]), "+f"(d[15]),
        "+f"(d[16]), "+f"(d[17]), "+f"(d[18]), "+f"(d[19]), "+f"(d[20]), "+f"(d[21]), "+f"(d[22]), "+f"(d[23]),
        "+f"(d[24]), "+f"(d[25]), "+f"(d[26]), "+f"(d[27]), "+f"(d[28]), "+f"(d[29]), "+f"(d[30]), "+f"(d[31]),
        "+f"(d[32]), "+f"(d[33]), "+f"(d[34]), "+f"(d[35]), "+f"(d[36]), "+f"(d[37]), "+f"(d[38]), "+f"(d[39]),
        "+f"(d[40]), "+f"(d[41]), "+f"(d[42]), "+f"(d[43]), "+f"(d[44]), "+f"(d[45]), "+f"(d[46]), "+f"(d[47]),
        "+f"(d[48]), "+f"(d[49]), "+f"(d[50]), "+f"(d[51]), "+f"(d[52]), "+f"(d[53]), "+f"(d[54]), "+f"(d[55]),
        "+f"(d[56]), "+f"(d[57]), "+f"(d[58]), "+f"(d[59]), "+f"(d[60]), "+f"(d[61]), "+f"(d[62]), "+f"(d[63]),
        "+f"(d[64]), "+f"(d[65]), "+f"(d[66]), "+f"(d[67]), "+f"(d[68]), "+f"(d[69]), "+f"(d[70]), "+f"(d[71]),
        "+f"(d[72]), "+f"(d[73]), "+f"(d[74]), "+f"(d[75]), "+f"(d[76]), "+f"(d[77]), "+f"(d[78]), "+f"(d[79]),
        "+f"(d[80]), "+f"(d[81]), "+f"(d[82]), "+f"(d[83]), "+f"(d[84]), "+f"(d[85]), "+f"(d[86]), "+f"(d[87]),
        "+f"(d[88]), "+f"(d[89]), "+f"(d[90]), "+f"(d[91]), "+f"(d[92]), "+f"(d[93]), "+f"(d[94]), "+f"(d[95]),
        "+f"(e[0]), "+f"(e[1]), "+f"(e[2]), "+f"(e[3]), "+f"(e[4]), "+f"(e[5]), "+f"(e[6]), "+f"(e[7]),
        "+f"(e[8]), "+f"(e[9]), "+f"(e[10]), "+f"(e[11]), "+f"(e[12]), "+f"(e[13]), "+f"(e[14]), "+f"(e[15]),
        "+f"(e[16]), "+f"(e[17]), "+f"(e[18]), "+f"(e[19]), "+f"(e[20]), "+f"(e[21]), "+f"(e[22]), "+f"(e[23]),
        "+f"(e[24]), "+f"(e[25]), "+f"(e[26]), "+f"(e[27]), "+f"(e[28]), "+f"(e[29]), "+f"(e[30]), "+f"(e[31])
      : "l"(descA), "l"(descB), "r"(scaleD));
}
__device__ __forceinline__ void wgmma_ss_n192(float (&d)[96], uint64_t descA, uint64_t descB, int scaleD) {
  asm volatile("{\n.reg .pred p;\nsetp.ne.b32 p, %98, 0;\n"
      "wgmma.mma_async.sync.aligned.m64n192k16.f32.bf16.bf16 {"
      "%0, %1, %2, %3, %4, %5, %6, %7, %8, %9, %10, %11, %12, %13, %14, %15,"
      "%16, %17, %18, %19, %20, %21, %22, %23, %24, %25, %26, %27, %28, %29, %30, %31,"
      "%32, %33, %34, %35, %36, %37, %38, %39, %40, %41, %42, %43, %44, %45, %46, %47,"
      "%48, %49, %50, %51, %52, %53, %54, %55, %56, %57, %58, %59, %60, %61, %62, %63,"
      "%64, %65, %66, %67, %68, %69, %70, %71, %72, %73, %74, %75, %76, %77, %78, %79,"
      "%80, %81, %82, %83, %84, %85, %86, %87, %88, %89, %90, %91, %92, %93, %94, %95"
      "}, %96, %97, p, 1, 1, 0, 1;\n}\n"
      : "+f"(d[0]), "+f"(d[1]), "+f"(d[2]), "+f"(d[3]), "+f"(d[4]), "+f"(d[5]), "+f"(d[6]), "+f"(d[7]),
        "+f"(d[8]), "+f"(d[9]), "+f"(d[10]), "+f"(d[11]), "+f"(d[12]), "+f"(d[13]), "+f"(d[14]), "+f"(d[15]),
        "+f"(d[16]), "+f"(d[17]), "+f"(d[18]), "+f"(d[19]), "+f"(d[20]), "+f"(d[21]), "+f"(d[22]), "+f"(d[23]),
        "+f"(d[24]), "+f"(d[25]), "+f"(d[26]), "+f"(d[27]), "+f"(d[28]), "+f"(d[29]), "+f"(d[30]), "+f"(d[31]),
        "+f"(d[32]), "+f"(d[33]), "+f"(d[34]), "+f"(d[35]), "+f"(d[36]), "+f"(d[37]), "+f"(d[38]), "+f"(d[39]),
        "+f"(d[40]), "+f"(d[41]), "+f"(d[42]), "+f"(d[43]), "+f"(d[44]), "+f"(d[45]), "+f"(d[46]), "+f"(d[47]),
        "+f"(d[48]), "+f"(d[49]), "+f"(d[50]), "+f"(d[51]), "+f"(d[52]), "+f"(d[53]), "+f"(d[54]), "+f"(d[55]),
        "+f"(d[56]), "+f"(d[57]), "+f"(d[58]), "+f"(d[59]), "+f"(d[60]), "+f"(d[61]), "+f"(d[62]), "+f"(d[63]),
        "+f"(d[64]), "+f"(d[65]), "+f"(d[66]), "+f"(d[67]), "+f"(d[68]), "+f"(d[69]), "+f"(d[70]), "+f"(d[71]),
        "+f"(d[72]), "+f"(d[73]), "+f"(d[74]), "+f"(d[75]), "+f"(d[76]), "+f"(d[77]), "+f"(d[78]), "+f"(d[79]),
        "+f"(d[80]), "+f"(d[81]), "+f"(d[82]), "+f"(d[83]), "+f"(d[84]), "+f"(d[85]), "+f"(d[86]), "+f"(d[87]),
        "+f"(d[88]), "+f"(d[89]), "+f"(d[90]), "+f"(d[91]), "+f"(d[92]), "+f"(d[93]), "+f"(d[94]), "+f"(d[95])
      : "l"(descA), "l"(descB), "r"(scaleD));
}
template <unsigned long long DESC, int SCALE>
__device__ __forceinline__ void wgmma_rs_n56(float (&d)[28], uint32_t a0, uint32_t a1, uint32_t a2, uint32_t a3) {
  asm volatile("{\n.reg .b64 desc;\nmov.b64 desc, %32;\n"
      "wgmma.mma_async.sync.aligned.m64n56k16.f32.bf16.bf16 {"
      "%0, %1, %2, %3, %4, %5, %6, %7, %8, %9, %10, %11, %12, %13, %14, %15,"
      "%16, %17, %18, %19, %20, %21, %22, %23, %24, %25, %26, %27"
      "}, {%28, %29, %30, %31}, desc, %33, 1, 1, 0;\n}\n"
      : "+f"(d[0]), "+f"(d[1]), "+f"(d[2]), "+f"(d[3]), "+f"(d[4]), "+f"(d[5]), "+f"(d[6]), "+f"(d[7]),
        "+f"(d[8]), "+f"(d[9]), "+f"(d[10]), "+f"(d[11]), "+f"(d[12]), "+f"(d[13]), "+f"(d[14]), "+f"(d[15]),
        "+f"(d[16]), "+f"(d[17]), "+f"(d[18]), "+f"(d[19]), "+f"(d[20]), "+f"(d[21]), "+f"(d[22]), "+f"(d[23]),
        "+f"(d[24]), "+f"(d[25]), "+f"(d[26]), "+f"(d[27])
      : "r"(a0), "r"(a1), "r"(a2), "r"(a3), "n"(DESC), "n"(SCALE));
}
template <unsigned long long DESC, int SCALE>
__device__ __forceinline__ void wgmma_rs_n32(float (&d)[28], uint32_t a0, uint32_t a1, uint32_t a2, uint32_t a3) {
  asm volatile("{\n.reg .b64 desc;\nmov.b64 desc, %20;\n"
      "wgmma.mma_async.sync.aligned.m64n32k16.f32.bf16.bf16 {"
      "%0, %1, %2, %3, %4, %5, %6, %7, %8, %9, %10, %11, %12, %13, %14, %15"
      "}, {%16, %17, %18, %19}, desc, %21, 1, 1, 0;\n}\n"
      : "+f"(d[0]), "+f"(d[1]), "+f"(d[2]), "+f"(d[3]), "+f"(d[4]), "+f"(d[5]), "+f"(d[6]), "+f"(d[7]),
        "+f"(d[8]), "+f"(d[9]), "+f"(d[10]), "+f"(d[11]), "+f"(d[12]), "+f"(d[13]), "+f"(d[14]), "+f"(d[15])
      : "r"(a0), "r"(a1), "r"(a2), "r"(a3), "n"(DESC), "n"(SCALE));
}

constexpr int NB = 4096, NF = 26, DIN = 1664;
constexpr int NGEMM = 128, NEXTRA = 4, GRID = NGEMM + NEXTRA;
constexpr int NC_EXTRA = 80;
constexpr int NC_WG0 = 16;
constexpr int HK = 4;
constexpr int PE0 = 9;
constexpr int WD = 2;
constexpr int GI = 3;
constexpr int PE1 = 4;
constexpr int PE2 = 8;
constexpr int PS2 = 6;
constexpr int POLL = 400;
constexpr int BGN = 1;
constexpr int PREG = 40;
constexpr int PS = 6;
constexpr int RB = 4;
constexpr int NC_GEMM = 29, NBIG = NB - NGEMM * NC_GEMM - NEXTRA * NC_EXTRA;
static_assert(NBIG >= 0 && NBIG <= NGEMM && NC_EXTRA % 4 == 0 && NC_EXTRA <= 96, "split");
constexpr int CW_MAIN = 22 * 1792, CW_LIN = 2 * 1024, CW_BYTES = CW_MAIN + CW_LIN;
constexpr int XSLOT = 4096;

constexpr int UNIT = 8192, FS = 18;
constexpr int U_W = 6, U_XB = 18, U_SP = 24;
constexpr int CW_CUT = 9;
constexpr int OFF_CW = 0, OFF_CW2 = 6 * UNIT, OFF_CWL = 9 * UNIT;
constexpr int CROW = 528;
constexpr int OFF_PARK = 10 * UNIT, OFF_PARK2 = 24 * UNIT;
constexpr int OFF_RS0 = OFF_CWL + CW_LIN, OFF_RS1 = OFF_CWL - 1024;
constexpr int OFF_GIDX = 26 * UNIT;
constexpr int OFF_TIDX = OFF_GIDX + 128 * NF * 4 - 8 * 64 * 4;
constexpr int OFF_CIDX = OFF_GIDX + 128 * NF * 4;
constexpr int OFF_EPI = OFF_CIDX + 32 * 8 * 4;
constexpr int OFF_DNN = OFF_EPI + 128 * 16;
constexpr int OFF_BAR = OFF_DNN + 112 * 8;
constexpr int SMEM_BYTES = OFF_BAR + 50 * 8;
static_assert(CW_CUT * 1792 <= 2 * UNIT && (22 - CW_CUT) * 1792 <= 3 * UNIT , "smem");
constexpr uint32_t SMEM_BASE = 1024;
static_assert(SMEM_BYTES <= 232448, "smem");
static_assert(OFF_EPI % 16 == 0 && OFF_BAR % 8 == 0, "align");
constexpr int XOFF_W3 = 0, XOFF_W2 = 35152, XOFF_W1 = 70304, XOFF_M = XOFF_W1 + 8 * 1352, XOFF_S = XOFF_M + 32 * 40 * 4,
              XOFF_SLOT = 10 * UNIT, XOFF_CIN0 = 2 * UNIT, XOFF_CIN1 = 18 * UNIT, XOFF_CIDX = 22 * UNIT,
              XOFF_BAR = 24 * UNIT, NPAIR = NC_EXTRA / 4;
static_assert(XOFF_S + 14 * 3136 <= 21 * UNIT && 48 * CROW <= 4 * UNIT, "smem");

constexpr int BAR_PARK = 7,
              BAR_FULL = 8,
              BAR_EV = 16,
              BAR_CW = 24,
              BAR_GIDX = 25,
              BAR_X0 = 26,
              BAR_W0 = 27,
              BAR_DNN = 28,
              BAR_T = 29,
              BAR_GDONE = 30,
              BAR_EPOCH = 31,
              BAR_CFULL = 32,
              BAR_C0 = 48;
constexpr int EV_CW = 29, EV_SLOT = 30, EV_END = 33;
__device__ __forceinline__ uint32_t ev_bar(uint32_t bars, int e) { return bars + 8 * (BAR_EV + (e & 7)); }
__device__ __forceinline__ uint32_t ev_par(int e) { return (e >> 3) & 1; }
constexpr unsigned long long STAGES = 0xb4b4924924924ull;
__host__ __device__ constexpr int b_x(int t) { return ((0xb2c1430bu >> (4 * t)) & 15) * 2; }
__host__ __device__ constexpr int b_w(int t) { return (0x0d0a120eu >> (8 * (t & 3))) & 31; }
__host__ __device__ constexpr int b_ws(int t) { return (t & 3) == 3 ? 4 : 1; }

struct Scratch {
  uint4 cw[CW_BYTES / 16];
  uint2 part[8 * NB];
  unsigned epoch[GRID];
  unsigned foldflag;
};
__device__ __align__(128) Scratch g_scratch;
__device__ __align__(1024) __nv_bfloat16 g_x0[NB * FS * 64];
struct GPtr { Scratch* s; const uint4* tab; uint32_t zero; };

__device__ __forceinline__ void wg_fence() { asm volatile("wgmma.fence.sync.aligned;" ::: "memory"); }
__device__ __forceinline__ void wg_commit() { asm volatile("wgmma.commit_group.sync.aligned;" ::: "memory"); }
template <int N> __device__ __forceinline__ void wg_wait() { asm volatile("wgmma.wait_group.sync.aligned %0;" ::"n"(N) : "memory"); }
__device__ __forceinline__ uint64_t mkdesc(uint32_t addr, uint32_t lbo, uint32_t sbo, uint32_t swz) {
  return (uint64_t)((addr & 0x3FFFF) >> 4) | ((uint64_t)(lbo >> 4) << 16) | ((uint64_t)(sbo >> 4) << 32) | ((uint64_t)swz << 62);
}
__device__ __forceinline__ bool elect1() {
  uint32_t p; asm volatile("{\n.reg .pred p;\nelect.sync _|p, 0xffffffff;\nselp.b32 %0, 1, 0, p;\n}" : "=r"(p)); return p;
}
__device__ __forceinline__ int fresh(int v) { asm volatile("" : "+r"(v)); return v; }
__device__ __forceinline__ void mbar_init(uint32_t bar, uint32_t cnt) { asm volatile("mbarrier.init.shared::cta.b64 [%0], %1;" ::"r"(bar), "r"(cnt) : "memory"); }
__device__ __forceinline__ void mbar_arrive(uint32_t bar) { asm volatile("mbarrier.arrive.shared::cta.b64 _, [%0];" ::"r"(bar) : "memory"); }
__device__ __forceinline__ void mbar_arrive_cta(uint32_t bar, uint32_t cta) {
  asm volatile("{\n.reg .b32 r;\nmapa.shared::cluster.u32 r, %0, %1;\nmbarrier.arrive.shared::cluster.b64 _, [r];\n}" ::"r"(bar), "r"(cta) : "memory");
}
__device__ __forceinline__ void mbar_expect_tx(uint32_t bar, uint32_t bytes) { asm volatile("mbarrier.arrive.expect_tx.shared::cta.b64 _, [%0], %1;" ::"r"(bar), "r"(bytes) : "memory"); }
__device__ __forceinline__ void mbar_wait(uint32_t bar, uint32_t parity) {
  asm volatile("{\n.reg .pred p;\nLAB_WAIT:\n"
               "mbarrier.try_wait.parity.shared::cta.b64 p, [%0], %1;\n"
               "@!p bra LAB_WAIT;\n}" ::"r"(bar), "r"(parity) : "memory");
}
__device__ __forceinline__ void flag_wait(const unsigned* p, unsigned target, unsigned sleep_ns) {
  asm volatile("{\n.reg .pred p;\n.reg .u32 n, v;\nmov.u32 n, 0;\nLAB_WAIT:\n"
               "ld.acquire.gpu.global.u32 v, [%0];\n"
               "sub.u32 v, v, %1;\n"
               "setp.ge.s32 p, v, 0;\n"
               "@p bra DONE;\n"
               "nanosleep.u32 %2;\n"
               "add.u32 n, n, 1;\n"
               "setp.lt.u32 p, n, 400000;\n"
               "@p bra LAB_WAIT;\n"
               "DONE:\n}" ::"l"(p), "r"(target), "r"(sleep_ns) : "memory");
}
__device__ __forceinline__ void put_tagged(uint2* p, float v, unsigned tag) {
  asm volatile("st.relaxed.gpu.global.v2.b32 [%0], {%1, %2};" ::"l"(p), "r"(__float_as_uint(v)), "r"(tag) : "memory");
}
__device__ __forceinline__ void flag_add(unsigned* p) { asm volatile("red.release.gpu.global.add.u32 [%0], 1;" ::"l"(p) : "memory"); }
__device__ __forceinline__ void tma_load(uint32_t dst, const CUtensorMap* tm, int c0, int c1, uint32_t bar) {
  asm volatile("cp.async.bulk.tensor.2d.shared::cluster.global.mbarrier::complete_tx::bytes [%0], [%1, {%3, %4}], [%2];"
               ::"r"(dst), "l"(tm), "r"(bar), "r"(c0), "r"(c1) : "memory");
}
__device__ __forceinline__ void tma_row_mc(uint32_t dst, const CUtensorMap* tm, int row, uint32_t bar) {
  asm volatile("cp.async.bulk.tensor.2d.shared::cluster.global.mbarrier::complete_tx::bytes.multicast::cluster [%0], [%1, {%3, %4}], [%2], %5;"
               ::"r"(dst), "l"(tm), "r"(bar), "r"(0), "r"(row), "h"((uint16_t)3));
}
__device__ __forceinline__ void tma_row(uint32_t dst, const CUtensorMap* tm, int row, uint32_t bar) {
  asm volatile("cp.async.bulk.tensor.2d.shared::cluster.global.mbarrier::complete_tx::bytes [%0], [%1, {%3, %4}], [%2];"
               ::"r"(dst), "l"(tm), "r"(bar), "r"(0), "r"(row));
}
__device__ __forceinline__ void tma_store(const CUtensorMap* tm, int c0, int c1, uint32_t src) {
  asm volatile("cp.async.bulk.tensor.2d.global.shared::cta.bulk_group [%0, {%1, %2}], [%3];\ncp.async.bulk.commit_group;"
               ::"l"(tm), "r"(c0), "r"(c1), "r"(src) : "memory");
}
template <int N> __device__ __forceinline__ void store_read() { asm volatile("cp.async.bulk.wait_group.read %0;" ::"n"(N) : "memory"); }
__device__ __forceinline__ void bulk_load(uint32_t dst, const void* src, uint32_t bytes, uint32_t bar) {
  asm volatile("cp.async.bulk.shared::cluster.global.mbarrier::complete_tx::bytes [%0], [%1], %2, [%3];"
               ::"r"(dst), "l"(src), "r"(bytes), "r"(bar));
}
__device__ __forceinline__ void l2_prefetch(const void* src, uint32_t bytes) {
  asm volatile("cp.async.bulk.prefetch.L2.global [%0], %1;" ::"l"(src), "r"(bytes));
}
__device__ __forceinline__ void w_prefetch(const __nv_bfloat16* w1, int f, int cta, int piece) {
  l2_prefetch(w1 + (f * 64 + (cta >> 3) * 4 + (cta & 1) * 2 + (piece & 1)) * DIN + (piece < 2 ? (cta & 6) * 192 : 1536 + (cta & 4) * 16),
              piece < 2 ? 768 : 128);
}
__device__ __forceinline__ void cpasync16(uint32_t dst, const void* src) {
  asm volatile("cp.async.cg.shared.global [%0], [%1], 16;" ::"r"(dst), "l"(src) : "memory");
}
template <int ID, int N> __device__ __forceinline__ void bar_sync() { asm volatile("bar.sync %0, %1;" ::"n"(ID), "n"(N) : "memory"); }
template <int ID, int N> __device__ __forceinline__ void bar_arrive() { asm volatile("bar.arrive %0, %1;" ::"n"(ID), "n"(N) : "memory"); }
__device__ __forceinline__ void ldsm4t(uint32_t& a, uint32_t& b, uint32_t& c, uint32_t& d, uint32_t addr) {
  asm volatile("ldmatrix.sync.aligned.m8n8.x4.trans.shared.b16 {%0,%1,%2,%3}, [%4];" : "=r"(a), "=r"(b), "=r"(c), "=r"(d) : "r"(addr) : "memory");
}
__device__ __forceinline__ int lds32(uint32_t addr) { int v; asm volatile("ld.shared.b32 %0, [%1];" : "=r"(v) : "r"(addr)); return v; }
__device__ __forceinline__ int2 lds64(uint32_t addr) { int2 v; asm volatile("ld.shared.v2.b32 {%0,%1}, [%2];" : "=r"(v.x), "=r"(v.y) : "r"(addr)); return v; }
__device__ __forceinline__ int4 lds128(uint32_t addr) {
  int4 v; asm volatile("ld.shared.v4.b32 {%0,%1,%2,%3}, [%4];" : "=r"(v.x), "=r"(v.y), "=r"(v.z), "=r"(v.w) : "r"(addr)); return v;
}
__device__ __forceinline__ float4 lds128f(uint32_t addr) {
  float4 v; asm volatile("ld.shared.v4.f32 {%0,%1,%2,%3}, [%4];" : "=f"(v.x), "=f"(v.y), "=f"(v.z), "=f"(v.w) : "r"(addr) : "memory"); return v;
}
__device__ __forceinline__ float4 lds128f(uint32_t addr, uint32_t off) {
  float4 v;
  asm volatile("{\n.reg .u32 t;\nadd.u32 t, %4, %5;\nld.shared.v4.f32 {%0,%1,%2,%3}, [t];\n}" : "=f"(v.x), "=f"(v.y), "=f"(v.z), "=f"(v.w) : "r"(addr), "r"(off) : "memory");
  return v;
}
__device__ __forceinline__ void sts32f(uint32_t addr, float v) { asm volatile("st.shared.f32 [%0], %1;" ::"r"(addr), "f"(v) : "memory"); }
__device__ __forceinline__ float bf_lo(uint32_t v) { return __uint_as_float(v << 16); }
__device__ __forceinline__ float bf_hi(uint32_t v) { return __uint_as_float(v & 0xffff0000u); }
__device__ __forceinline__ float bf2f(__nv_bfloat16 v) { return __bfloat162float(v); }

__device__ __forceinline__ uint32_t mul2(uint32_t a, uint32_t b) {
  uint32_t r; asm volatile("mul.rn.bf16x2 %0, %1, %2;" : "=r"(r) : "r"(a), "r"(b)); return r;
}
__device__ __forceinline__ uint32_t mul2lo(uint32_t a, uint32_t b) {
  uint32_t r;
  asm volatile("{\n.reg .b16 l, h;\n.reg .b32 t;\nmov.b32 {l, h}, %2;\nmov.b32 t, {l, l};\nmul.rn.bf16x2 %0, %1, t;\n}" : "=r"(r) : "r"(a), "r"(b));
  return r;
}
__device__ __forceinline__ uint32_t mul2hi(uint32_t a, uint32_t b) {
  uint32_t r;
  asm volatile("{\n.reg .b16 l, h;\n.reg .b32 t;\nmov.b32 {l, h}, %2;\nmov.b32 t, {h, h};\nmul.rn.bf16x2 %0, %1, t;\n}" : "=r"(r) : "r"(a), "r"(b));
  return r;
}

__host__ __device__ constexpr int xfield(int r, int e, int c) {
  return r == 9 ? 24 + e : 8 * (r / 3) + 2 * (((r % 3) + c) & 3) + (((r % 3) == 2 && c >= 2) ? 1 - e : e);
}
__host__ __device__ constexpr int blk_a(int b) { return b < 12 ? 3 * (b / 8) + ((b & 3) == 3) : (b < 15 ? 3 * (b - 12) : 3 * (b - 15)); }
__host__ __device__ constexpr int blk_b(int b) { return b < 12 ? 3 * (b < 4 ? 1 : 2) + ((b & 3) == 3 ? 0 : (b & 3)) : (b < 15 ? 3 * (b - 12) + 1 : 9); }
__host__ __device__ constexpr int slot_pq(int u, int e, int c) {
  return u < 36 ? (xfield(blk_a(u >> 1), e, c) | (xfield(blk_b(u >> 1), u & 1, c) << 8))
       : u < 39 ? (xfield(3 * (u - 36), e, c) * 257)
       : u < 42 ? (xfield(3 * (u - 39), e, c) | (xfield(3 * (u - 39) + 2, e, c) << 8))
       : u == 42 ? (xfield(3 * e, 0, c) | (xfield(3 * e, 1, c) << 8))
       : u == 43 ? (e == 0 ? (xfield(6, 0, c) | (xfield(6, 1, c) << 8))
                           : (c == 0 ? 24 * 257 : c == 1 ? 25 * 257 : c == 2 ? (24 | 25 << 8) : 26 * 257))
       : u < 47 ? (xfield(3 * (u - 44), e, c) | (26 << 8))
       : (c == 0 ? ((24 + e) | 26 << 8) : 27 * 257);
}
struct SlotTab { uint32_t v[48 * 8]; };
constexpr SlotTab make_slot_tab() {
  SlotTab t{};
  for (int u = 0; u < 48; u++)
    for (int k = 0; k < 8; k++) {
      const int pq = slot_pq(u, k & 1, k >> 1), p = pq & 255, q = pq >> 8;
      t.v[u * 8 + k] = (uint32_t)((p * 28 + q) * 4) | ((uint32_t)(((p != q && q < 26) ? q * 28 + p : 27 * 28 + 27) * 4) << 16);
    }
  return t;
}
__device__ __align__(16) const SlotTab g_slot_tab = make_slot_tab();

struct CinCtx {
  uint32_t o03, o14, o25, o69, o78, cin, selA, selB;
  bool ones, lead;
  uint32_t so, so2, co, co2, bar, jump, dslot, last;
  bool ring;
};
constexpr unsigned long long CW_DESC = (unsigned long long)((SMEM_BASE + OFF_CW) >> 4) | (8ull << 16) | (16ull << 32);
constexpr unsigned long long CWL_DESC = CW_DESC + (OFF_CWL - OFF_CW) / 16;

template <int U>
__device__ __forceinline__ uint32_t zreg(const uint32_t (&x)[10][2], int h, const CinCtx& c) {
  if constexpr (U < 36) {
    if constexpr (U & 1) return mul2hi(x[blk_a(U >> 1)][h], x[blk_b(U >> 1)][h]);
    else return mul2lo(x[blk_a(U >> 1)][h], x[blk_b(U >> 1)][h]);
  } else if constexpr (U < 39) {
    return mul2(x[3 * (U - 36)][h], x[3 * (U - 36)][h]);
  } else if constexpr (U < 42) {
    return mul2(x[3 * (U - 39)][h], x[3 * (U - 39) + 2][h]);
  } else if constexpr (U == 42) {
    return mul2(__byte_perm(x[0][h], x[3][h], 0x5410), __byte_perm(x[0][h], x[3][h], 0x7632));
  } else {
    const uint32_t f = c.ones ? 0x3f803f80u : x[9][h];
    return mul2(__byte_perm(x[6][h], f, c.selA), __byte_perm(x[6][h], f, c.selB));
  }
}

template <int G>
__device__ __forceinline__ void z_fill(uint32_t (&z)[8], const uint32_t (&x)[10][2], const CinCtx& c) {
  z[0] = zreg<4 * G>(x, 0, c);     z[1] = zreg<4 * G>(x, 1, c);
  z[2] = zreg<4 * G + 1>(x, 0, c); z[3] = zreg<4 * G + 1>(x, 1, c);
  z[4] = zreg<4 * G + 2>(x, 0, c); z[5] = zreg<4 * G + 2>(x, 1, c);
  z[6] = zreg<4 * G + 3>(x, 0, c); z[7] = zreg<4 * G + 3>(x, 1, c);
}
__host__ __device__ constexpr unsigned long long cw_desc(int s) { return CW_DESC + (s < CW_CUT ? s * 1792 : OFF_CW2 - OFF_CW + (s - CW_CUT) * 1792) / 16; }
template <int G>
__device__ __forceinline__ void z_mma(float (&acc)[28], const uint32_t (&z)[8]) {
  wgmma_rs_n56<cw_desc(2 * G), G != 0>(acc, z[0], z[1], z[2], z[3]);
  wgmma_rs_n56<cw_desc(2 * G + 1), 1>(acc, z[4], z[5], z[6], z[7]);
}

__device__ __forceinline__ void cin_finish(const CinCtx& c, float (&acc)[28], uint32_t out) {
#pragma unroll
  for (int i = 0; i < 28; i++) asm volatile("" : "+f"(acc[i]));
  float s0 = acc[12] * acc[13], s1 = acc[14] * acc[15];
#pragma unroll
  for (int i = 0; i < 12; i += 2) {
    s0 = fmaf(acc[i], acc[16 + i], s0);
    s1 = fmaf(acc[i + 1], acc[17 + i], s1);
  }
  sts32f(c.cin + out, s0 + s1);
}

__device__ __forceinline__ void cin_ldsm(const CinCtx& c, uint32_t so, uint32_t (&x)[10][2]) {
  ldsm4t(x[0][0], x[0][1], x[3][0], x[3][1], so + c.o03);
  ldsm4t(x[1][0], x[1][1], x[4][0], x[4][1], so + c.o14);
  ldsm4t(x[2][0], x[2][1], x[5][0], x[5][1], so + c.o25);
  ldsm4t(x[6][0], x[6][1], x[9][0], x[9][1], so + c.o69);
  ldsm4t(x[7][0], x[7][1], x[8][0], x[8][1], so + c.o78);
}
__device__ __forceinline__ void cin_load(const CinCtx& c, int k, bool real, uint32_t (&x)[10][2]) {
  if (k == 0 && real) mbar_wait(c.bar, 0);
  cin_ldsm(c, k ? c.so2 : c.so, x);
  if (k == 1 && c.lead) mbar_arrive(c.bar + 8 * NPAIR);
}
__device__ __forceinline__ void cin_advance(CinCtx& c) {
  const uint32_t d = c.so == c.jump ? c.dslot : 2 * XSLOT;
  c.so += d; c.so2 += d;
  c.co = c.ring ? c.co + 2 * CROW : c.so;
  c.bar += 8;
}
constexpr int CG_WAIT = 3;
constexpr int CG_FIN = 3;
constexpr int CG_HEAD = 4;
constexpr int CG_LIN = 5;
constexpr int CG_LOAD = 5;
constexpr int CG_N = 11;
static_assert(CG_FIN >= CG_WAIT && CG_FIN < CG_HEAD && CG_LOAD >= CG_HEAD && CG_LIN >= CG_HEAD && CG_LOAD < 10, "CIN schedule");
template <int G, int GEND, typename F>
__device__ __forceinline__ void cin_groups(const CinCtx& c, const uint32_t (&x)[10][2], float (&acc)[28], uint32_t (&z)[8],
                                           int q, bool more, uint32_t (&xn)[10][2], F finish) {
  if constexpr (G < GEND) {
    wg_fence();
    if constexpr (G == CG_LIN) {
      wgmma_rs_n32<CWL_DESC, 1>(acc, x[0][0], x[0][1], x[3][0], x[3][1]);
      wgmma_rs_n32<CWL_DESC + 1024 / 16, 1>(acc, x[6][0], x[6][1], x[9][0], x[9][1]);
    }
    z_mma<G>(acc, z);
    wg_commit();
    if constexpr (G == CG_LOAD) cin_load(c, q, more, xn);
    uint32_t zn[8];
    if constexpr (G + 1 < CG_N) z_fill<G + 1>(zn, x, c); else z_fill<0>(zn, xn, c);
    if constexpr (G == CG_FIN) finish();
    wg_wait<CG_WAIT>();
    if constexpr (G + 1 < GEND) cin_groups<G + 1, GEND>(c, x, acc, zn, q, more, xn, finish);
    else {
#pragma unroll
      for (int i = 0; i < 8; i++) z[i] = zn[i];
    }
    if constexpr (G + 1 < GEND) {
#pragma unroll
      for (int i = 0; i < 8; i++) z[i] = zn[i];
    }
  }
}
template <typename F>
__device__ __forceinline__ void cin_head(const CinCtx& c, uint32_t (&x)[10][2], float (&acc)[28], uint32_t (&z)[8], F finish) {
  cin_groups<0, CG_HEAD>(c, x, acc, z, 0, false, x, finish);
}
__device__ __forceinline__ void cin_tail(const CinCtx& c, const uint32_t (&x)[10][2], float (&acc)[28], uint32_t (&z)[8],
                                         int q, bool more, uint32_t (&xn)[10][2]) {
  cin_groups<CG_HEAD, CG_N>(c, x, acc, z, q, more, xn, []() {});
}

__device__ __forceinline__ int slot_of(int wg, int j) {
  return wg ? (j == 0 ? 9 * UNIT + XSLOT : j <= 8 ? 2 * UNIT + (j - 1) * XSLOT : 21 * UNIT + (j - 9) * XSLOT)
            : (j < 3 ? OFF_GIDX + j * XSLOT : 14 * UNIT + (j - 3) * XSLOT);
}

__device__ __forceinline__ void cin_begin(CinCtx& c, uint32_t sb, int wg, uint32_t first, uint32_t (&x)[10][2], float (&acc)[28], uint32_t (&z)[8]) {
  int t; asm volatile("mov.u32 %0, %%tid.x;" : "=r"(t));
  const int m = t & 16, f0 = t & 7, f1 = (f0 + 2) & 7, f2 = (f0 ^ 4) ^ (f0 >> 2);
  const uint32_t base = sb + m * 64, ch = (t & 96) + (t & 8) * 2;
  c.o03 = (base + f0 * 0x90) ^ ch;
  c.o14 = (base + f1 * 0x90) ^ ch;
  c.o25 = (base + f2 * 0x90) ^ ch;
  c.o69 = (base + 2048 + (m ? f0 & 1 : f0) * 0x90) ^ ch;
  c.o78 = m ? c.o25 + 1024 : c.o14 + 2048;
  mbar_wait(sb + OFF_BAR + 8 * BAR_GDONE, 0);
  mbar_wait(sb + OFF_BAR + 8 * (BAR_C0 + wg), 0);
  cin_ldsm(c, first, x);
  mbar_wait(sb + OFF_BAR + 8 * BAR_CW, 0);
  z_fill<0>(z, x, c);
  cin_head(c, x, acc, z, []() {});
}
__device__ __forceinline__ void cin_setup(CinCtx& c, uint32_t sb, int wg, int p, bool gemm, int nj, uint32_t zero) {
  c.bar = sb + (gemm ? OFF_BAR + 8 * (BAR_CFULL + wg * 8) : XOFF_BAR + wg * 16 * NPAIR);
  c.lead = (p & 31) == 0 && !gemm; c.ring = !gemm;
  c.so = !gemm ? XOFF_SLOT + 8 * wg * XSLOT : wg ? 2 * UNIT : OFF_GIDX + XSLOT;
  c.jump = c.so + (gemm && !wg ? 0 : 6 * XSLOT);
  c.dslot = !gemm ? -6 * XSLOT : wg ? 19 * UNIT - 6 * XSLOT : 14 * UNIT - OFF_GIDX - XSLOT;
  c.co = gemm ? c.so : (wg ? XOFF_CIN1 : XOFF_CIN0) - NF * 128;
  c.co2 = gemm ? XSLOT : CROW;
  c.so2 = c.so + XSLOT + zero;
  c.last = gemm ? slot_of(wg, (nj - 1) | 1) : c.co + ((nj - 1) & ~1) * CROW;
  c.cin = sb + NF * 128 + p * 4;
  const int q = p & 3;
  c.selA = q == 1 ? 0x7610 : 0x5410;
  c.selB = q == 0 ? 0x5432 : 0x7632;
  c.ones = q == 3;
}
template <typename F2, typename F3>
__device__ __forceinline__ void cin_run(CinCtx& c, int nj, uint32_t (&xA)[10][2], float (&accA)[28], uint32_t (&z)[8], F2 before_end, F3 st5) {
  float accB[28];
  uint32_t xB[10][2];
  const uint32_t lastA = nj & 1 ? c.last : 0;
#pragma unroll 1
  for (int j = 0;; j += 2) {
    cin_tail(c, xA, accA, z, 0, c.co != lastA, xB);
    if (c.co == lastA) { before_end(); wg_wait<0>(); cin_finish(c, accA, c.co); break; }
    cin_head(c, xB, accB, z, [&]() { st5(j); cin_finish(c, accA, c.co); });
    cin_tail(c, xB, accB, z, 1, true, xA);
    if (c.co == c.last) { before_end(); wg_wait<0>(); cin_finish(c, accB, c.co + c.co2); break; }
    cin_head(c, xA, accA, z, [&]() { st5(j + 1); cin_finish(c, accB, c.co + c.co2); });
    cin_advance(c);
  }
}

constexpr float ALPHA = 0.3292034911525734f, KAPPA = 2.423681954311584f;
__device__ __forceinline__ float gelu_acc(float v, float ab, float w, float s, float alpha = ALPHA) {
  const float a = fmaf(v, alpha, ab);
  const float u = a * fmaf(a, a, KAPPA);
  float th; asm("tanh.approx.f32 %0, %1;" : "=f"(th) : "f"(u));
  return fmaf(fmaf(a, th, a), w, s);
}

constexpr int QD = 2;
template <int NG>
struct Gelu {
  float4 q[QD + 1];
  uint32_t ep;
  __device__ __forceinline__ void start(uint32_t a) {
    ep = a;
#pragma unroll
    for (int i = 0; i < QD; i++) q[i] = lds128f(ep + i * 64);
  }
  template <int I0, int I1>
  __device__ __forceinline__ void part(float (&d)[4 * NG], float& r0, float& r1, uint32_t done) {
    float alpha;
    asm volatile("{\n.reg .pred p;\nmbarrier.test_wait.parity.shared::cta.b64 p, [%1], 0;\nselp.f32 %0, %2, 0f7FC00000, p;\n}"
                 : "=f"(alpha) : "r"(done), "f"(ALPHA) : "memory");
    part<I0, I1>(d, r0, r1, alpha);
  }
  template <int I0, int I1>
  __device__ __forceinline__ void part(float (&d)[4 * NG], float& r0, float& r1, float alpha = ALPHA) {
#pragma unroll
    for (int i = I0; i < I1; i++) {
      if (i + QD < NG) q[(i + QD) % (QD + 1)] = lds128f(ep + (i + QD) * 64);
      const float4 v = q[i % (QD + 1)];
#pragma unroll
      for (int e = 0; e < 4; e++) asm volatile("" : "+f"(d[4 * i + e]));
      const float al = i < I0 + QD ? alpha : ALPHA;
      r0 = gelu_acc(d[4 * i + 0], v.x, v.z, r0, al);
      r0 = gelu_acc(d[4 * i + 1], v.y, v.w, r0, al);
      r1 = gelu_acc(d[4 * i + 2], v.x, v.z, r1, al);
      r1 = gelu_acc(d[4 * i + 3], v.y, v.w, r1, al);
    }
    asm volatile("" : "+f"(r0), "+f"(r1));
  }
};
__device__ __forceinline__ float quad_sum(float r0, float r1, float r2, float r3, int lane) {
  const bool b0 = lane & 1, b1 = lane & 2;
  const float a = (b0 ? r1 : r0) + __shfl_xor_sync(0xffffffffu, b0 ? r0 : r1, 1);
  const float b = (b0 ? r3 : r2) + __shfl_xor_sync(0xffffffffu, b0 ? r2 : r3, 1);
  return (b1 ? b : a) + __shfl_xor_sync(0xffffffffu, b1 ? a : b, 2);
}
__device__ __forceinline__ void sts128f(uint32_t addr, float a, float b, float c, float d) {
  asm volatile("st.shared.v4.f32 [%0], {%1, %2, %3, %4};" ::"r"(addr), "f"(a), "f"(b), "f"(c), "f"(d) : "memory");
}
__device__ __forceinline__ void pin(float a, float b, uint32_t addr, uint32_t zero) {
  asm volatile("{\n.reg .pred p;\nsetp.ne.u32 p, %3, 0;\n@p st.shared.v2.f32 [%0], {%1, %2};\n}" ::"r"(addr), "f"(a), "f"(b), "r"(zero) : "memory");
}
__device__ __forceinline__ void hand_on(float (&d)[96], const float (&s)[96]) {
#pragma unroll
  for (int i = 0; i < 96; i++) asm volatile("mov.b32 %0, %1;" : "=f"(d[i]) : "f"(s[i]));
}
__device__ __forceinline__ uint64_t desc_x(int u) { return mkdesc(SMEM_BASE, 16, 1024, 1) + u * (UNIT / 16); }
__device__ __forceinline__ uint64_t desc_w(int u, int stride = 1) { return mkdesc(SMEM_BASE, stride * UNIT, 1024, 1) + u * (UNIT / 16); }
__device__ __forceinline__ void tile_step(float (&d)[96], uint64_t dA, uint64_t dB) {
  wg_fence();
#pragma unroll
  for (int k = 0; k < 4; k++) wgmma_ss_n192(d, dA + 2 * k, dB + 128 * k, 1);
  wg_commit();
}
template <int K0 = 0, int K1 = 4>
__device__ __forceinline__ void wide_step(float (&d)[96], float (&e)[32], uint64_t dA, uint64_t dB) {
  wg_fence();
#pragma unroll
  for (int k = K0; k < K1; k++) wgmma_ss_n256(d, e, dA + 2 * k, dB + 128 * k, 1);
  wg_commit();
}
__device__ __forceinline__ int cin_row(int c, int j) {
  if (c >= NGEMM) {
    const int e = (c - NGEMM) * NC_EXTRA + j;
    c = e < 256 ? e >> 1 : NBIG + e - 256;
    j = e < 256 ? 30 + (e & 1) : 29;
  }
  return (c >> 3) * 256 + (c & 2) * 64 + (c & 1) * 64 + (c & 4) * 8 + j;
}
__device__ __forceinline__ int cin_count(int c) {
  return c < NGEMM ? NC_GEMM + (c < NBIG) : NC_EXTRA;
}

__device__ __forceinline__ int fold_i0(int e) { return e < 2 ? 7 * e : 2 + 6 * e; }
__device__ __forceinline__ uint32_t ldg16(const void* p) { uint16_t v; asm volatile("ld.global.nc.u16 %0, [%1];" : "=h"(v) : "l"(p)); return v; }
__device__ __forceinline__ uint4 ldg128(const void* p) {
  uint4 v; asm volatile("ld.global.nc.v4.u32 {%0,%1,%2,%3}, [%4];" : "=r"(v.x), "=r"(v.y), "=r"(v.z), "=r"(v.w) : "l"(p)); return v;
}
__device__ __forceinline__ void sts64f(uint32_t addr, float a, float b) { asm volatile("st.shared.v2.f32 [%0], {%1, %2};" ::"r"(addr), "f"(a), "f"(b) : "memory"); }
__device__ __forceinline__ float to_tf32(float v) { uint32_t r; asm("cvt.rna.tf32.f32 %0, %1;" : "=r"(r) : "f"(v)); return __uint_as_float(r); }
__device__ __forceinline__ uint4 fold_chunk(uint32_t base, const uint4 t0, const uint4 t1) {
  const uint32_t t[8] = {t0.x, t0.y, t0.z, t0.w, t1.x, t1.y, t1.z, t1.w};
  uint32_t v[4];
#pragma unroll
  for (int c = 0; c < 4; c++) {
    const float w0 = __int_as_float(lds32(base + (t[2 * c] & 0xffff))) + __int_as_float(lds32(base + (t[2 * c] >> 16)));
    const float w1 = __int_as_float(lds32(base + (t[2 * c + 1] & 0xffff))) + __int_as_float(lds32(base + (t[2 * c + 1] >> 16)));
    __nv_bfloat162 pk = __floats2bfloat162_rn(w0, w1);
    v[c] = *reinterpret_cast<uint32_t*>(&pk);
  }
  return make_uint4(v[0], v[1], v[2], v[3]);
}
__device__ __forceinline__ int cw_chunk(int u, int n) {
  return ((u < 44 ? (u >> 1) * 1792 : CW_MAIN + ((u - 44) >> 1) * 1024) + (n >> 3) * 256 + (u & 1) * 128 + (n & 7) * 16) >> 4;
}
__device__ __forceinline__ void fold_weights(uint8_t* smem, uint32_t sb, int e, const __nv_bfloat16* __restrict__ wco, const GPtr gp) {
  const int tid = threadIdx.x, lane = tid & 31, warp = tid >> 5;
  const uint32_t bars = sb + OFF_BAR;
  const int i0 = fold_i0(e), i = i0 + warp;
  const bool own = i < fold_i0(e + 1);
  const uint32_t wb16 = ldg16(wco + (lane < NF ? 26 + lane : 0)), wc16 = ldg16(wco + (lane < NF ? 52 + lane : 0));
  const uint32_t w116 = ldg16(wco + (own ? i : 0));
  const uint4* tab = gp.tab;
  const uint4 ta0 = ldg128(tab + 2 * lane), ta1 = ldg128(tab + 2 * lane + 1);
  const uint4 tb0 = ldg128(tab + 64 + 2 * (lane & 15)), tb1 = ldg128(tab + 65 + 2 * (lane & 15));
  asm volatile("barrier.cluster.arrive.relaxed.aligned;\nbarrier.cluster.wait.acquire.aligned;" ::: "memory");
  if (warp >= 6) {
    for (int t = tid - 192; t < 6 * 20; t += 64) sts64f(sb + XOFF_M + 26 * 160 + t * 8, 0.f, 0.f);
    if (warp == 6 && lane < NF) {
      sts64f(sb + XOFF_M + lane * 160 + 104, bf_lo(wb16), 0.f);
      sts64f(sb + XOFF_M + lane * 160 + 112, 0.f, 0.f);
      sts64f(sb + XOFF_M + lane * 160 + 120, 0.f, 0.f);
    }
    if (warp == 7) {
      gp.s->cw[cw_chunk(lane, 28 + e)] = make_uint4(0, 0, 0, 0);
      if (lane < 16) gp.s->cw[cw_chunk(32 + lane, 28 + e)] = make_uint4(0, 0, 0, 0);
    }
  } else {
    mbar_wait(bars + 8 * BAR_GIDX, 0);
    float m0 = 0.f, m1 = 0.f, m2 = 0.f, m3 = 0.f;
    const uint32_t a = sb + XOFF_W3 + (tid < 169 ? tid : 0) * 8;
#pragma unroll 2
    for (int g = 0; g < NF; g++) {
      const int2 v = lds64(a + g * 1352);
      const float w = __shfl_sync(0xffffffffu, bf_lo(wc16), g);
      m0 = fmaf(w, bf_lo(v.x), m0); m1 = fmaf(w, bf_hi(v.x), m1);
      m2 = fmaf(w, bf_lo(v.y), m2); m3 = fmaf(w, bf_hi(v.y), m3);
    }
    if (tid < 169) {
      const int o = tid * 2, o2 = o + 1;
      sts64f(sb + XOFF_M + (o / 13) * 160 + (o % 13) * 8, to_tf32(m0), to_tf32(m1));
      sts64f(sb + XOFF_M + (o2 / 13) * 160 + (o2 % 13) * 8, to_tf32(m2), to_tf32(m3));
    }
  }
  const uint32_t sT = sb + XOFF_S + warp * 2 * 3136, sA = sT + 3136;
  const int g = lane >> 2, c = lane & 3;
  uint32_t af[2][8];
  mbar_wait(bars + 8 * BAR_FULL, 0);
  if (own) {
#pragma unroll
    for (int k = 0; k < 8; k++) {
      const int h = 4 * k + c;
      const uint32_t a = sb + XOFF_W2 + ((h < NF ? h : 0) * 676 + i * 26 + 2 * g) * 2;
      af[0][k] = lds32(a);
      af[1][k] = lds32(a + (g < 5 ? 32 : 0));
    }
#pragma unroll 1
    for (int o = lane; o < 338; o += 32) {
      const uint32_t v = lds32(sb + XOFF_W1 + (i - (i0 & ~1)) * 1352 + o * 4);
      sts64f(sA + (o / 13) * 112 + (o % 13) * 8, bf_lo(v), bf_hi(v));
    }
    if (lane < 28) sts64f(sA + lane * 112 + 104, 0.f, 0.f);
    if (lane < 2) sts64f(sT + (26 + lane) * 112 + 104, lane == 0 ? bf_lo(w116) : 0.f, 0.f);
  }
  bar_sync<4, 256>();
  if (own) {
#pragma unroll 1
    for (int n = 0; n < 4; n++) {
      float d[2][4] = {};
#pragma unroll
      for (int ks = 0; ks < 4; ks++) {
        const uint32_t b0 = lds32(sb + XOFF_M + (8 * ks + c) * 160 + (8 * n + g) * 4);
        const uint32_t b1 = lds32(sb + XOFF_M + (8 * ks + c + 4) * 160 + (8 * n + g) * 4);
#pragma unroll
        for (int m = 0; m < 2; m++)
          asm volatile("mma.sync.aligned.m16n8k8.row.col.f32.tf32.tf32.f32 {%0,%1,%2,%3}, {%4,%5,%6,%7}, {%8,%9}, {%0,%1,%2,%3};"
                       : "+f"(d[m][0]), "+f"(d[m][1]), "+f"(d[m][2]), "+f"(d[m][3])
                       : "r"(af[m][2 * ks] << 16), "r"(af[m][2 * ks] & 0xffff0000u), "r"(af[m][2 * ks + 1] << 16),
                         "r"(af[m][2 * ks + 1] & 0xffff0000u), "r"(b0), "r"(b1));
      }
      if (n < 3 || c < 2) {
        const uint32_t a = sT + 2 * g * 112 + (8 * n + 2 * c) * 4;
        sts64f(a, d[0][0], d[0][1]);
        sts64f(a + 112, d[0][2], d[0][3]);
        if (g < 5) {
          sts64f(a + 16 * 112, d[1][0], d[1][1]);
          sts64f(a + 17 * 112, d[1][2], d[1][3]);
        }
      }
    }
    __syncwarp();
    const int nt = i < 24 ? i : 2 * i - 24, na = i < 24 ? 32 + i : 2 * i - 23;
#pragma unroll 1
    for (int k = 0; k < 3; k++) {
      const bool isa = k == 1 || (k == 2 && lane >= 16);
      const uint4 v = fold_chunk(isa ? sA : sT, k < 2 ? ta0 : tb0, k < 2 ? ta1 : tb1);
      if (k < 2 || lane < 28 || na < 32) gp.s->cw[cw_chunk(k < 2 ? lane : 32 + (lane & 15), isa ? na : nt)] = v;
    }
  }
  __syncwarp();
  if (lane == 0) flag_add(&gp.s->foldflag);
  bar_sync<4, 256>();
  mbar_wait(bars + 8 * BAR_GDONE, 0);
  if (tid >= 128 && tid < 132) mbar_arrive(ev_bar(bars, EV_END));
}

__global__ void __cluster_dims__(2, 1, 1) __launch_bounds__(384, 1)
xdeepfm_kernel(const int* __restrict__ idx, const __nv_bfloat16* __restrict__ table, const __nv_bfloat16* __restrict__ w1,
               const __nv_bfloat16* __restrict__ b1, const __nv_bfloat16* __restrict__ w2,
               const __nv_bfloat16* __restrict__ ws, const __nv_bfloat16* __restrict__ wco,
               const __nv_bfloat16* __restrict__ bout, __nv_bfloat16* __restrict__ out, const GPtr gp,
               const __grid_constant__ CUtensorMap tmW, const __grid_constant__ CUtensorMap tmT,
               const __grid_constant__ CUtensorMap tmS, const __grid_constant__ CUtensorMap tmC) {
  int myidx, idx1, idx2 = 0, idx3 = 0;
  {
    const int t = threadIdx.x, b = blockIdx.x, half = (b >> 1) ^ (t >= 256 ? t >> 4 : 0);
    const int* ip = idx + (((b >> 3) & 15) * 256 + (half & 1) * 128 + (t < 256 ? t >> 1 : (b & 1) * 64 + ((t >> 1) & 48) + (t & 15))) * NF;
    asm volatile("{\n.reg .pred p;\nsetp.ge.u32 p, %5, 256;\nld.global.nc.v2.s32 {%0, %1}, [%4];\n@p ld.global.nc.v2.s32 {%2, %3}, [%4 + 8];\n}"
                 : "=r"(myidx), "=r"(idx1), "+r"(idx2), "+r"(idx3) : "l"(ip), "r"(t));
  }
  extern __shared__ __align__(1024) uint8_t smem[];
  const uint32_t sb = (uint32_t)__cvta_generic_to_shared(smem);
  const uint32_t bars = sb + OFF_BAR;
  const int tid = threadIdx.x, lane = tid & 31;
  const int warp = __shfl_sync(0xffffffffu, tid >> 5, 0);
  const int cta = blockIdx.x;
  const bool gemm = cta < NGEMM;
  const int nt = cta & 7, rank = cta & 1;

  if (warp == 8 && elect1()) {
    mbar_init(bars + 8 * BAR_GIDX, 1);
    mbar_init(bars + 8 * BAR_FULL, 1);
    mbar_init(bars + 8 * BAR_W0, 1);
    asm volatile("fence.mbarrier_init.release.cluster;" ::: "memory");
    if (gemm) {
      mbar_expect_tx(bars + 8 * BAR_W0, 4 * UNIT);
#pragma unroll
      for (int i = 0; i < 4; i++)
        tma_load(sb + (U_W + i) * UNIT, &tmW, i < 3 ? nt * 192 + i * 64 : 1536 + (nt >> 2) * 64, 0, bars + 8 * BAR_W0);
    } else {
      mbar_expect_tx(bars + 8 * BAR_GIDX, 35152);
      bulk_load(sb + XOFF_W3, ws + 2 * 17576, 35152, bars + 8 * BAR_GIDX);
    }
  }
  if (threadIdx.x < 256) {}
  else if (threadIdx.x >= 384 - 16) {
    const int l = threadIdx.x & 7;
    if (l < 7) asm volatile("prefetch.global.L2 [%0];" ::"l"(w1 + (((cta >> 3 & 15) * 2 + (cta & 1)) * 2 + ((threadIdx.x >> 3) & 1)) * DIN + (l < 6 ? (cta & 6) * 192 + l * 64 : 1536 + (cta & 4) * 16)));
  }
  else if (threadIdx.x >= 352 && threadIdx.x < 359) {
    const int l = blockIdx.x * 7 + threadIdx.x - 352;
    if (l < 824) asm volatile("prefetch.global.L2 [%0];" ::"l"(ws + (823 - l) * 64));
  }

  if (warp >= 8) {
    const int pw = warp - 8;
    const bool lead = elect1();
    if (lead) {
      if (pw) mbar_init(bars + 8 * (pw < 3 ? BAR_FULL + pw : BAR_X0), 1);
      else mbar_init(bars + 8 * BAR_GDONE, 4);
      asm volatile("fence.mbarrier_init.release.cluster;" ::: "memory");
    }
    __syncwarp();
    asm volatile("barrier.cluster.arrive.relaxed.aligned;" ::: "memory");
    if (lead) {
      if (gemm) w_prefetch(w1, 1, cta, pw);
      if (pw == 0) {
        if (gemm) {
          mbar_expect_tx(bars + 8 * BAR_FULL, 2 * UNIT);
          asm volatile("prefetch.tensormap [%0];" ::"l"(&tmT) : "memory");
          asm volatile("prefetch.tensormap [%0];" ::"l"(&tmS) : "memory");
        } else {
          const int i0 = fold_i0(cta - NGEMM) & ~1, ni = NF - i0 < 8 ? NF - i0 : 8;
          mbar_expect_tx(bars + 8 * BAR_FULL, 35152 + ni * 1352);
          bulk_load(sb + XOFF_W1, ws + i0 * 676, ni * 1352, bars + 8 * BAR_FULL);
          bulk_load(sb + XOFF_W2, ws + 17576, 35152, bars + 8 * BAR_FULL);
        }
      }
    }
    __syncwarp();
    asm volatile("setmaxnreg.dec.sync.aligned.u32 24;");
    if (elect1()) {
      mbar_init(bars + 8 * (BAR_EV + pw), 4);
      mbar_init(bars + 8 * (BAR_EV + 4 + pw), 4);
      mbar_init(bars + 8 * (BAR_FULL + 4 + pw), 1);
      if (pw < 3) mbar_init(bars + 8 * (pw == 2 ? BAR_CW : BAR_DNN + pw), pw == 0 && !gemm ? 4 : 1 + (pw & 1));
      if (pw < 2) mbar_init(bars + 8 * (pw ? BAR_PARK : BAR_FULL + 3), 1 + 7 * pw);
#pragma unroll
      for (int i = 0; i < 4; i++) mbar_init(bars + 8 * (BAR_CFULL + pw * 4 + i), 1);
      if (pw < 2) mbar_init(bars + 8 * (BAR_C0 + pw), 1);
      asm volatile("fence.mbarrier_init.release.cluster;" ::: "memory");
    }
    __syncwarp();
    bar_sync<6, 128>();
    asm volatile("barrier.cluster.wait.acquire.aligned;" ::: "memory");
    if (gemm) {
      {
        const uint32_t a = sb + OFF_GIDX + ((lane >> 4) * 64 + pw * 16 + (lane & 15)) * NF * 4;
        asm volatile("st.shared.v2.b32 [%0], {%1, %2};\nst.shared.v2.b32 [%0 + 8], {%3, %4};"
                     ::"r"(a), "r"(myidx), "r"(idx1), "r"(idx2), "r"(idx3) : "memory");
        __syncwarp();
      }
      if (elect1()) {
#pragma unroll
        for (int j = 0; j < 16; j += 8) {
          int r[8];
#pragma unroll
          for (int i = 0; i < 8; i++) r[i] = lds32(sb + OFF_GIDX + ((64 + pw * 16 + j + i) * NF) * 4);
#pragma unroll
          for (int i = 0; i < 8; i++) tma_row_mc(sb + U_XB * UNIT + (rank * 64 + pw * 16 + j + i) * 128, &tmT, r[i], bars + 8 * BAR_FULL);
        }
        int s = 1;
#pragma unroll 1
        for (int fi = 1; fi < NF; fi++) {
          const int f = fresh(fi), pw = fresh(warp) - 8, ct = fresh(cta), nt = ct & 7;
          const int t = f - FS, st = t < 0 ? s : (t & 3) ^ ((t >> 1) & 1), e = f - 3 - (t > 1);
          const uint32_t fb = bars + 8 * (BAR_FULL + (f & 7)), ia = sb + OFF_GIDX + (pw * 16 * NF + f) * 4;
          const uint32_t d = sb + (st == 3 ? U_SP : 2 * st) * UNIT + ((ct & 1) * 64 + pw * 16) * 128;
          if (f == 4) mbar_wait(bars + 8 * BAR_GIDX, 0);
          int r[2][RB];
#pragma unroll
          for (int i = 0; i < RB; i++) r[0][i] = lds32(ia + i * NF * 4);
          if (e >= 0) mbar_wait(ev_bar(bars, e), ev_par(e));
          if (pw == 0) mbar_expect_tx(fb, t < 0 ? 8 * UNIT : 6 * UNIT);
#pragma unroll
          for (int j = 0; j < 16 / RB; j++) {
#pragma unroll
            for (int i = 0; i < RB; i++) r[(j + 1) & 1][i] = lds32(ia + (RB * j + RB + i + (RB * j + RB >= 16) * 48) * NF * 4);
#pragma unroll
            for (int i = 0; i < RB; i++) tma_row_mc(d + (RB * j + i) * 128, &tmT, r[j & 1][i], fb);
          }
          if (t < 0) {
#pragma unroll
            for (int j = 0; j < 16 / RB; j++) {
              if (j + 1 < 16 / RB) {
#pragma unroll
                for (int i = 0; i < RB; i++) r[(j + 1) & 1][i] = lds32(ia + (64 + RB * j + RB + i) * NF * 4);
              }
#pragma unroll
              for (int i = 0; i < RB; i++) tma_row_mc(d + U_XB * UNIT + (RB * j + i) * 128, &tmT, r[j & 1][i], fb);
            }
          }
          tma_load(sb + (U_W + 4 * st + pw) * UNIT, &tmW, pw < 3 ? nt * 192 + pw * 64 : 1536 + (nt >> 2) * 64, f * 64, fb);
          if (f == GI && pw < 2) {
            if (pw == 0) mbar_expect_tx(bars + 8 * BAR_GIDX, 128 * NF * 4);
            bulk_load(sb + OFF_GIDX + pw * 64 * NF * 4, idx + ((ct >> 3) * 256 + (((ct >> 1) ^ pw) & 1) * 128 + (ct & 1) * 64) * NF, 64 * NF * 4, bars + 8 * BAR_GIDX);
          }
          if (f == GI && pw == 2) asm volatile("prefetch.tensormap [%0];" ::"l"(&tmC) : "memory");
          if (f + WD < NF) w_prefetch(w1, f + WD, ct, pw);
          if (++s == 3) s = 0;
        }
        mbar_wait(bars + 8 * BAR_T, 0);
#pragma unroll 1
        for (int ti = 0; ti < 8; ti++) {
          const int t = fresh(ti), pw = fresh(warp) - 8, e = t < 4 ? 22 - !t : 19 + t;
          const uint32_t ia = sb + OFF_TIDX + t * 256 + pw * 64, fb = bars + 8 * (BAR_FULL + ((NF + t) & 7));
          const uint32_t d = sb + b_x(t) * UNIT + ((fresh(cta) & 1) * 64 + pw * 16) * 128;
          int4 r[2];
          r[0] = lds128(ia);
          r[1] = lds128(ia + 16);
          mbar_wait(ev_bar(bars, e), ev_par(e));
          if (pw == 0) mbar_expect_tx(fb, t < 3 ? 2 * UNIT : 5 * UNIT);
#pragma unroll
          for (int j = 0; j < 4; j++) {
            tma_row_mc(d + (4 * j + 0) * 128, &tmT, r[j & 1].x, fb);
            tma_row_mc(d + (4 * j + 1) * 128, &tmT, r[j & 1].y, fb);
            tma_row_mc(d + (4 * j + 2) * 128, &tmT, r[j & 1].z, fb);
            tma_row_mc(d + (4 * j + 3) * 128, &tmT, r[j & 1].w, fb);
            if (j < 2) r[j & 1] = lds128(ia + 32 + 16 * j);
          }
        }
        mbar_arrive(bars + 8 * BAR_GDONE);
      }
      __syncwarp();
    }
    asm volatile("setmaxnreg.inc.sync.aligned.u32 %0;" ::"n"(PREG));
    {
    int cta; asm volatile("mov.u32 %0, %%ctaid.x;" : "=r"(cta));
    int tid; asm volatile("mov.u32 %0, %%tid.x;" : "=r"(tid));
    const int lane = tid & 31, pw = __shfl_sync(0xffffffffu, tid >> 5, 0) - 8;
    const bool gemm = cta < NGEMM;
    const int bt = cta >> 3, nt = cta & 7;
    const int ncin = cin_count(cta);
    unsigned epoch;
    auto load_cw = [&]() {
      if (elect1()) {
        asm volatile("fence.proxy.async.global;" ::: "memory");
        mbar_expect_tx(bars + 8 * BAR_CW, CW_BYTES);
        bulk_load(sb + OFF_CW, gp.s->cw, CW_CUT * 1792, bars + 8 * BAR_CW);
        bulk_load(sb + OFF_CW2, gp.s->cw + CW_CUT * 1792 / 16, (22 - CW_CUT) * 1792, bars + 8 * BAR_CW);
        bulk_load(sb + OFF_CWL, gp.s->cw + CW_MAIN / 16, CW_LIN, bars + 8 * BAR_CW);
      }
    };
    if (!gemm) {
      epoch = gp.s->epoch[cta] + 1;
#pragma unroll 1
      for (int i = pw * 32 + lane; i < NC_EXTRA * 13; i += 128)
        asm volatile("cp.async.ca.shared.global [%0], [%1], 8;" ::"r"(sb + XOFF_CIDX + i * 8), "l"(idx + cin_row(cta, i / 13) * NF + i % 13 * 2) : "memory");
      if (elect1()) {
#pragma unroll 1
        for (int i = 0; i < NPAIR; i++) mbar_init(sb + XOFF_BAR + (pw * NPAIR + i) * 8, pw & 1 ? 4 : 1);
        asm volatile("fence.mbarrier_init.release.cluster;" ::: "memory");
      }
      asm volatile("cp.async.wait_all;" ::: "memory");
      bar_sync<6, 128>();
      if (elect1()) mbar_arrive(bars + 8 * BAR_GDONE);
      __syncwarp();
      if (pw == 3) {
        flag_wait(&gp.s->foldflag, epoch * NEXTRA * 8, 0);
        __syncwarp();
        load_cw();
      }
      if (elect1()) {
        const int wg = pw & 1;
#pragma unroll 1
        for (int t = pw < 2 ? -1 : 1; t < NPAIR; t += t < 0 ? 1 : 2) {
          const int j = t < 0 ? 0 : 2 * t + 1, n = t < 0 || t == NPAIR - 1 ? 1 : 2;
          const uint32_t cb = t < 0 ? bars + 8 * (BAR_C0 + wg) : sb + XOFF_BAR + (wg * 2 * NPAIR + t) * 8;
          if (t == 0 || t == 1) mbar_wait(ev_bar(bars, EV_END), ev_par(EV_END));
          if (t >= 4) mbar_wait(cb + 8 * (NPAIR - 4), 0);
          mbar_expect_tx(cb, n * NF * 128);
#pragma unroll 1
          for (int i = 0; i < n; i++) {
            const uint32_t d = sb + (t < 0 ? OFF_GIDX + wg * XSLOT : XOFF_SLOT + (wg * 8 + (t & 3) * 2 + i) * XSLOT);
            const uint32_t ia = sb + XOFF_CIDX + (wg * (NC_EXTRA / 2) + j + i) * NF * 4;
#pragma unroll 1
            for (int k = 0; k < NF; k += 2) {
              const int2 r = lds64(ia + k * 4);
              tma_row(d + k * 128, &tmT, r.x, cb);
              tma_row(d + (k + 1) * 128, &tmT, r.y, cb);
            }
          }
        }
      }
      __syncwarp();
    } else {
      epoch = lds32(bars + 8 * BAR_EPOCH);
      if (pw == 3) {
        mbar_wait(ev_bar(bars, EV_CW), ev_par(EV_CW));
        load_cw();
      }
      constexpr int n0 = NC_WG0;
      const uint32_t ep = sb + OFF_EPI + (lane & 3) * 16, pk = sb + (pw * 32 + lane) * 16;
      float r2 = 0.f, r3 = 0.f;
      mbar_wait(bars + 8 * BAR_GDONE, 0);
      mbar_wait(bars + 8 * BAR_X0, 0);
      asm volatile("fence.proxy.async.global;" ::: "memory");
#pragma unroll 1
      for (int k = 0; k < 5; k++) {
        const int n = pw + 4 * k, wg = n > 1 && ((n & 1) || n == 2), j = n == 1 ? 1 : n < 3 ? 0 : n - 1 - wg;
        const int m = min((wg ? ncin - n0 : n0) - j, j ? 2 : 1), r = wg * n0 + j;
        const uint32_t cb = bars + 8 * (j ? BAR_CFULL + wg * 8 + (j >> 1) : BAR_C0 + wg), d = sb + slot_of(wg, j);
        if (n >= 2 && n < 12) {
          const int e = n == 2 ? EV_CW : n < 7 ? EV_SLOT : EV_END;
          mbar_wait(ev_bar(bars, e), ev_par(e));
        }
        auto load_sample = [&](int i) {
          const int4 u = lds128(sb + OFF_CIDX + (r + i) * 32), v = lds128(sb + OFF_CIDX + (r + i) * 32 + 16);
          const uint32_t a = d + i * XSLOT;
          tma_row(a, &tmC, (cta * 32 + r + i) * FS, cb);
          tma_row(a + (FS + 0) * 128, &tmT, u.x, cb);
          tma_row(a + (FS + 1) * 128, &tmT, u.y, cb);
          tma_row(a + (FS + 2) * 128, &tmT, u.z, cb);
          tma_row(a + (FS + 3) * 128, &tmT, u.w, cb);
          tma_row(a + (FS + 4) * 128, &tmT, v.x, cb);
          tma_row(a + (FS + 5) * 128, &tmT, v.y, cb);
          tma_row(a + (FS + 6) * 128, &tmT, v.z, cb);
          tma_row(a + (FS + 7) * 128, &tmT, v.w, cb);
        };
        if (m > 0 && elect1()) {
          mbar_expect_tx(cb, m * NF * 128);
#pragma unroll 1
          for (int i = 0; i < m; i++) load_sample(i);
        }
        __syncwarp();
        if (k == 0 || k == 4) continue;
        if (k == 1) {
          mbar_wait(bars + 8 * BAR_PARK, 0);
        }
        uint32_t a = k == 3 ? OFF_PARK2 : OFF_PARK + (k - 1) * 8 * 2048, b = (k - 1) * 8 * 64;
#pragma unroll 1
        for (const uint32_t e = b + 8 * 64; b != e; a += BGN * 2048, b += BGN * 64) {
          float4 v[BGN], q[BGN];
#pragma unroll
          for (int i = 0; i < BGN; i++) { v[i] = lds128f(pk, a + i * 2048); q[i] = lds128f(ep, b + i * 64); }
#pragma unroll
          for (int i = 0; i < BGN; i++) {
            r2 = gelu_acc(v[i].x, q[i].x, q[i].z, r2);
            r3 = gelu_acc(v[i].z, q[i].x, q[i].z, r3);
            r2 = gelu_acc(v[i].y, q[i].y, q[i].w, r2);
            r3 = gelu_acc(v[i].w, q[i].y, q[i].w, r3);
          }
        }
      }
      const float4 w = lds128f(pk + OFF_RS0);
      const int2 v = lds64(sb + OFF_RS1 + (pw * 32 + lane) * 8);
      uint2* dst = gp.s->part + (nt * NB + bt * 256 + pw * 16);
      const uint32_t o = (lane & 1) * 8 + (lane & 2) * 32 + (lane >> 2);
      put_tagged(dst + (o ^ ((cta & 2) * 64 + (~cta & 1) * 64)), quad_sum(w.x, w.y, w.z, w.w, lane), epoch);
      put_tagged(dst + (o ^ ((~cta & 2) * 64)), quad_sum(__int_as_float(v.x), __int_as_float(v.y), r2, r3, lane), epoch);
    }
    if (pw == 3 || !gemm) {
      float s = (sb & 0xFFFFFF) == SMEM_BASE ? bf2f(bout[0]) : __int_as_float(0x7fc00000);
      const int r = gemm ? lane : pw * (NC_EXTRA / 4) + min(lane, NC_EXTRA / 4 - 1), row = cin_row(cta, r);
      const uint2* src = gp.s->part + row;
      uint2 v[8];
#pragma unroll 1
      for (int i = 0; i < 100000; i++) {
        unsigned miss = 0;
#pragma unroll
        for (int n = 0; n < 8; n++)
          asm volatile("ld.relaxed.gpu.global.v2.b32 {%0, %1}, [%2];" : "=r"(v[n].x), "=r"(v[n].y) : "l"(src + n * NB) : "memory");
#pragma unroll
        for (int n = 0; n < 8; n++) miss |= v[n].y ^ epoch;
        if (__all_sync(0xffffffffu, miss == 0)) break;
        __nanosleep(POLL);
      }
#pragma unroll
      for (int n = 0; n < 8; n++) s += __uint_as_float(v[n].x);
      sts64f(sb + OFF_DNN + r * 8, s, __int_as_float(row));
      __syncwarp();
      if (lane == 0) mbar_arrive(bars + 8 * BAR_DNN);
      if (pw == 3 && lane == 0) gp.s->epoch[fresh(cta)] = epoch;
    }
    }
  } else {
    const int wg = warp >> 2;
    const int p = tid & 127;
    if (gemm) {
      asm volatile("barrier.cluster.arrive.relaxed.aligned;" ::: "memory");
#pragma unroll
      for (int i = 0; i < 4; i++) {
        const int r = __shfl_sync(0xffffffffu, myidx, 8 * i + 2 * (lane >> 3));
        const int row = warp * 16 + 4 * i + (lane >> 3);
        cpasync16(sb + row * 128 + (((lane & 7) ^ (row & 7)) << 4), table + (size_t)r * 64 + (lane & 7) * 8);
      }
      asm volatile("barrier.cluster.wait.acquire.aligned;" ::: "memory");
    } else {
      fold_weights(smem, sb, cta - NGEMM, wco, gp);
    }
    asm volatile("setmaxnreg.inc.sync.aligned.u32 224;");
    float r0 = 0.f, r1 = 0.f, r2 = 0.f, r3 = 0.f;
    CinCtx c;
    float accA[28];
    uint32_t xA[10][2], z[8];
    const uint32_t ep = sb + OFF_EPI + (lane & 3) * 16;
    auto load_w = [&](int t) {
      const int w = warp & 3;
      if (w < 3 && elect1())
        tma_load(sb + (b_w(t) + b_ws(t) * w) * UNIT, &tmW, nt * 192 + w * 64, (NF - 1 - t) * 64, bars + 8 * (BAR_FULL + ((NF + t) & 7)));
    };
    auto keep_x = [&](int f, int u) {
      if (warp == 0 && elect1()) tma_store(&tmS, f * 64, cta * 32, sb + (u + rank) * UNIT + (nt >> 2) * 4096);
    };
    auto role = [&](int w) { int c; asm volatile("mov.u32 %0, %%ctaid.x;" : "=r"(c)); return c < NGEMM && wg == w; };
    if (role(0)) {
      asm volatile("setmaxnreg.inc.sync.aligned.u32 256;");
      float d0[96], dx[32], dw[96];
      Gelu<24> g0;
      mbar_wait(bars + 8 * BAR_W0, 0);
      asm volatile("cp.async.wait_all;" ::: "memory");
      asm volatile("fence.proxy.async.shared::cta;" ::: "memory");
      bar_sync<2, 256>();
      const uint64_t dA0 = desc_x(rank), dA1 = desc_x(rank ^ 1);
      wg_fence();
#pragma unroll
      for (int k = 0; k < 4; k++) {
        wgmma_ss_n256(dw, dx, dA0 + 2 * k, desc_w(U_W) + 128 * k, k != 0);
        wgmma_ss_n192(d0, dA1 + 2 * k, desc_w(U_W) + 128 * k, k != 0);
      }
      wg_commit();
      keep_x(0, 0);
#pragma unroll 1
      for (int f = 1; f < NF - 3; f++) {
        mbar_wait(bars + 8 * (BAR_FULL + (f & 7)), (f >> 3) & 1);
        const int st = (STAGES >> (2 * f)) & 3, xo = (st == 3 ? U_SP : 2 * st) * (UNIT / 16);
        const uint64_t dB = desc_w(U_W + 4 * st);
        wg_fence();
        wgmma_ss_n256(dw, dx, dA0 + xo, dB, 1);
        wgmma_ss_n192(d0, dA1 + xo, dB, 1);
        wg_commit();
        store_read<0>();
        wg_wait<1>();
        if (p < (f > FS ? 4 : 2)) mbar_arrive_cta(ev_bar(bars, f - 1), p & 1);
#pragma unroll
        for (int k = 1; k < 4; k++) {
          wgmma_ss_n256(dw, dx, dA0 + xo + 2 * k, dB + 128 * k, 1);
          wgmma_ss_n192(d0, dA1 + xo + 2 * k, dB + 128 * k, 1);
        }
        wg_commit();
        if (f < FS) keep_x(f, 2 * st);
      }
      {
        constexpr int x3 = 2 * (UNIT / 16), x4 = U_SP * (UNIT / 16), x5 = 4 * (UNIT / 16);
        const uint64_t dB3 = desc_w(U_W + 4), dB4 = desc_w(U_W + 12), dB5 = desc_w(U_W + 8);
        mbar_wait(bars + 8 * (BAR_FULL + 7), 0);
        tile_step(d0, dA1 + x3, dB3);
        wg_wait<1>();
        if (p < 4) mbar_arrive_cta(ev_bar(bars, NF - 4), p & 1);
        mbar_wait(bars + 8 * (BAR_FULL + 0), 1);
        tile_step(d0, dA1 + x4, dB4);
        mbar_wait(bars + 8 * (BAR_FULL + 1), 1);
        tile_step(d0, dA1 + x5, dB5);
        wide_step(dw, dx, dA0 + x3, dB3);
        g0.start(ep);
        wg_wait<1>();
        wide_step(dw, dx, dA0 + x4, dB4);
        g0.part<0, PE1>(d0, r0, r1, bars + 8 * BAR_W0);
        pin(r0, r1, ep, gp.zero);
        wg_wait<1>();
        if (p < 4) mbar_arrive_cta(ev_bar(bars, NF - 3), p & 1);
        wide_step<0, HK>(dw, dx, dA0 + x5, dB5);
        g0.part<PE1, PE2>(d0, r0, r1, bars + 8 * BAR_W0);
        pin(r0, r1, ep, gp.zero);
        wg_wait<1>();
        bar_arrive<4, 256>();
        if (p < 4) mbar_arrive_cta(ev_bar(bars, NF - 2), p & 1);
        wide_step<HK, 4>(dw, dx, dA0 + x5, dB5);
        g0.part<PE2, PE0>(d0, r0, r1);
        pin(r0, r1, ep, gp.zero);
        wg_wait<0>();
        load_w(3);
        if (p < 4) mbar_arrive_cta(ev_bar(bars, NF - 1), p & 1);
        asm volatile("cp.async.bulk.wait_group 0;" ::: "memory");
        if (warp == 0 && elect1()) mbar_arrive(bars + 8 * BAR_X0);
      }
      g0.part<PE0, 24>(d0, r0, r1);
      Gelu<8> gx;
      gx.start(ep + 24 * 64);
      gx.part<0, 8>(dx, r2, r3);
      float d1[96];
      hand_on(d1, dw);
      asm volatile("setmaxnreg.dec.sync.aligned.u32 224;");
      Gelu<24> g1;
      g1.start(ep);
      g1.part<0, 24>(d1, r2, r3);
    }
    if (role(1)) {
      float d0[96], dw[96];
      asm volatile("cp.async.wait_all;" ::: "memory");
      asm volatile("fence.proxy.async.shared::cta;" ::: "memory");
      bar_arrive<2, 256>();
      {
        const int col = p < 96 ? nt * 96 + p : 768 + (nt >> 2) * 32 + (p - 96);
        const uint32_t bb = __ldg(reinterpret_cast<const uint32_t*>(b1) + col), ww = __ldg(reinterpret_cast<const uint32_t*>(w2) + col);
        reinterpret_cast<float4*>(smem + OFF_EPI)[p] =
            make_float4(ALPHA * bf_lo(bb), ALPHA * bf_hi(bb), (0.5f / ALPHA) * bf_lo(ww), (0.5f / ALPHA) * bf_hi(ww));
      }
      mbar_wait(bars + 8 * BAR_W0, 0);
      mbar_wait(bars + 8 * BAR_FULL, 0);
      wg_fence();
#pragma unroll
      for (int k = 0; k < 4; k++) {
        wgmma_ss_n192(d0, desc_x(U_XB) + 2 * k, desc_w(U_W) + 128 * k, k != 0);
        wgmma_ss_n192(dw, desc_x(U_XB + 1) + 2 * k, desc_w(U_W) + 128 * k, k != 0);
      }
      wg_commit();
      int s = 1;
#pragma unroll 1
      for (int f = 1; f < FS; f++) {
        mbar_wait(bars + 8 * (BAR_FULL + (f & 7)), (f >> 3) & 1);
        const uint64_t dA = desc_x(U_XB + 2 * s), dB = desc_w(U_W + 4 * s);
        wg_fence();
        wgmma_ss_n192(d0, dA, dB, 1);
        wgmma_ss_n192(dw, dA + 512, dB, 1);
        wg_commit();
        wg_wait<1>();
        if (p < 2) mbar_arrive_cta(ev_bar(bars, f - 1), p);
#pragma unroll
        for (int k = 1; k < 4; k++) {
          wgmma_ss_n192(d0, dA + 2 * k, dB + 128 * k, 1);
          wgmma_ss_n192(dw, dA + 512 + 2 * k, dB + 128 * k, 1);
        }
        wg_commit();
        if (++s == 3) s = 0;
      }
      wg_wait<0>();
      if (p < 2) mbar_arrive_cta(ev_bar(bars, FS - 1), p);
      {
        const uint32_t a = sb + OFF_GIDX + 64 * NF * 4;
        int v[4];
#pragma unroll
        for (int i = 0; i < 4; i++) v[i] = lds32(a + (((p & 15) * 4 + i) * NF + (NF - 1 - (p >> 4))) * 4);
        const int2 w = lds64(sb + OFF_GIDX + (((nt >> 2) * 32 + (p >> 2)) * NF + FS + (p & 3) * 2) * 4);
        asm volatile("st.shared.v2.b32 [%0], {%1, %2};" ::"r"(sb + OFF_CIDX + p * 8), "r"(w.x), "r"(w.y) : "memory");
        bar_sync<3, 128>();
        asm volatile("st.shared.v4.b32 [%0], {%1, %2, %3, %4};" ::"r"(sb + OFF_TIDX + p * 16), "r"(v[0]), "r"(v[1]), "r"(v[2]), "r"(v[3]) : "memory");
        bar_sync<3, 128>();
        if (p < 2) {
          const unsigned epoch = gp.s->epoch[cta] + 1;
          flag_wait(&gp.s->foldflag, epoch * NEXTRA * 8, 0);
          sts32f(bars + 8 * BAR_EPOCH, __uint_as_float(epoch));
          mbar_arrive(bars + 8 * BAR_T);
        }
        __syncwarp();
      }
      mbar_wait(ev_bar(bars, FS), ev_par(FS));
      mbar_wait(bars + 8 * (BAR_FULL + 2), 1);
      bar_sync<4, 256>();
#pragma unroll
      for (int t = 0; t < 4; t++) {
        if (t) mbar_wait(bars + 8 * (BAR_FULL + 2 + t), 1);
        const uint64_t dA = desc_x(b_x(t)), dB = desc_w(b_w(t), b_ws(t));
        wg_fence();
#pragma unroll
        for (int k = 0; k < 4; k++) {
          wgmma_ss_n192(d0, dA + 2 * k, dB + 128 * k, 1);
          wgmma_ss_n192(dw, dA + 512 + 2 * k, dB + 128 * k, 1);
          if (k == 1 && t) {
            wg_commit();
            wg_wait<1>();
            wg_fence();
          }
        }
        wg_commit();
        if (t) {
          if (t == 1) mbar_wait(ev_bar(bars, NF - 1), ev_par(NF - 1));
          load_w(3 + t);
          if (t == 1 && p < 4) mbar_arrive_cta(ev_bar(bars, 26), p & 1);
        }
      }
      mbar_wait(bars + 8 * (BAR_FULL + 6), 1);
      tile_step(d0, desc_x(b_x(4)), desc_w(b_w(4)));
      wg_wait<1>();
      load_w(7);
      if (p < 4) mbar_arrive(ev_bar(bars, EV_CW));
      mbar_wait(bars + 8 * (BAR_FULL + 7), 1);
      tile_step(d0, desc_x(b_x(5)), desc_w(b_w(5)));
      mbar_wait(bars + 8 * (BAR_FULL + 0), 0);
      tile_step(d0, desc_x(b_x(6)), desc_w(b_w(6)));
      mbar_wait(bars + 8 * (BAR_FULL + 1), 0);
      tile_step(d0, desc_x(b_x(7)), desc_w(b_w(7), 4));
      tile_step(dw, desc_x(b_x(4) + 1), desc_w(b_w(4)));
      Gelu<24> g0;
      g0.start(ep);
      wg_wait<1>();
      tile_step(dw, desc_x(b_x(5) + 1), desc_w(b_w(5)));
      g0.part<0, PS>(d0, r0, r1);
      pin(r0, r1, ep, gp.zero);
      wg_wait<1>();
      if (p < 4) mbar_arrive(ev_bar(bars, 30));
      tile_step(dw, desc_x(b_x(6) + 1), desc_w(b_w(6)));
      g0.part<PS, PS + PS2>(d0, r0, r1);
      pin(r0, r1, ep, gp.zero);
      wg_wait<1>();
      tile_step(dw, desc_x(b_x(7) + 1), desc_w(b_w(7), 4));
      g0.part<PS + PS2, 24>(d0, r0, r1);
      sts64f(sb + OFF_RS1 + p * 8, r0, r1);
      cin_begin(c, sb, 1, slot_of(1, 0), xA, accA, z);
      if (p < 4) mbar_arrive(ev_bar(bars, EV_END));
#pragma unroll
      for (int i = 0; i < 24; i++)
        sts128f(sb + p * 16 + (i < 16 ? OFF_PARK + i * 2048 : OFF_PARK2 + (i - 16) * 2048), dw[4 * i], dw[4 * i + 1], dw[4 * i + 2], dw[4 * i + 3]);
      __syncwarp();
      if (lane == 0) mbar_arrive(bars + 8 * BAR_PARK);
    }
    if (!role(1)) {
      cin_begin(c, sb, wg, OFF_GIDX + wg * XSLOT, xA, accA, z);
      sts128f(sb + OFF_RS0 + p * 16, r0, r1, r2, r3);
      __syncwarp();
      if (lane == 0) mbar_arrive(bars + 8 * BAR_PARK);
    }

    {
    int cta, tid;
    asm volatile("mov.u32 %0, %%ctaid.x;" : "=r"(cta));
    asm volatile("mov.u32 %0, %%tid.x;" : "=r"(tid));
    cta = __shfl_sync(0xffffffffu, cta, 0);
    const bool gemm = cta < NGEMM;
    const int p = tid & 127, wg = __shfl_sync(0xffffffffu, tid >> 7, 0);
    const int ncin = cin_count(cta);
    const int n0 = gemm ? NC_WG0 : NC_EXTRA / 2;
    const int rb = wg ? n0 : 0;
    const int nj = wg ? ncin - n0 : n0;
    cin_setup(c, sb, wg, p, gemm, nj, gp.zero);
    uint32_t fa = sb + (gemm ? slot_of(wg, (p >> 3) + 1) + NF * 128 : (wg ? XOFF_CIN1 : XOFF_CIN0) + (p >> 3) * CROW) + (p & 7) * 16, fd = sb + OFF_DNN + rb * 8;
    asm volatile("" : "+r"(fa), "+r"(fd));
    auto wg_sync = [&]() { if (wg == 0) bar_sync<1, 128>(); else bar_sync<3, 128>(); };
    mbar_wait(gemm ? bars + 8 * BAR_GDONE : ev_bar(bars, EV_END), 0);
    cin_run(c, nj, xA, accA, z, [&]() {
      mbar_wait(bars + 8 * BAR_DNN, 0);
    }, [&](int j) {
    });
    int2 dn = lds64(fd + (p >> 3) * 8);
    __nv_bfloat16* op = out + dn.y;
    float d = (p & 7) == 0 ? __int_as_float(dn.x) : 0.f;
    asm volatile("" : "+f"(d), "+l"(op));
    wg_sync();
#pragma unroll 1
    for (int r = 0;;) {
      const float4 v0 = lds128f(fa), v1 = lds128f(fa + 128), v2 = lds128f(fa + 256), v3 = lds128f(fa + 384);
      float s = (((v0.x + v0.y) + (v0.z + v0.w)) + ((v1.x + v1.y) + (v1.z + v1.w))) +
                (((v2.x + v2.y) + (v2.z + v2.w)) + (((v3.x + v3.y) + d) + (v3.z + v3.w)));
      s += __shfl_xor_sync(0xffffffffu, s, 1);
      s += __shfl_xor_sync(0xffffffffu, s, 2);
      s += __shfl_xor_sync(0xffffffffu, s, 4);
      if ((p & 7) == 0 && r + (p >> 3) < nj) *op = __float2bfloat16(s);
      r += 16;
      if (r >= nj) break;
      fa += 16 * CROW;
      dn = lds64(fd + (r + (p >> 3)) * 8);
      op = out + dn.y;
      d = (p & 7) == 0 ? __int_as_float(dn.x) : 0.f;
    }
    }
  }
}

typedef CUresult (*EncodeFn)(CUtensorMap*, CUtensorMapDataType, cuuint32_t, void*, const cuuint64_t*, const cuuint64_t*,
                             const cuuint32_t*, const cuuint32_t*, CUtensorMapInterleave, CUtensorMapSwizzle,
                             CUtensorMapL2promotion, CUtensorMapFloatOOBfill);

extern "C" void kernel_launch(void* const* d_in, const int* in_sizes, int n_in, void* d_out, int out_size) {
  void* fn = nullptr;
  cudaDriverEntryPointQueryResult q;
  cudaGetDriverEntryPoint("cuTensorMapEncodeTiled", &fn, cudaEnableDefault, &q);
  EncodeFn enc = (EncodeFn)fn;
  CUtensorMap tmW, tmT, tmS, tmC;
  const cuuint32_t es[3] = {1, 1, 1};
  {
    cuuint64_t dims[2] = {DIN, DIN}, st[1] = {DIN * 2};
    cuuint32_t box[2] = {64, 64};
    enc(&tmW, CU_TENSOR_MAP_DATA_TYPE_BFLOAT16, 2, d_in[4], dims, st, box, es, CU_TENSOR_MAP_INTERLEAVE_NONE,
        CU_TENSOR_MAP_SWIZZLE_128B, CU_TENSOR_MAP_L2_PROMOTION_NONE, CU_TENSOR_MAP_FLOAT_OOB_FILL_NONE);
  }
  {
    cuuint64_t dims[2] = {64, (cuuint64_t)(in_sizes[1] / 64)}, st[1] = {128};
    cuuint32_t box[2] = {64, 1};
    enc(&tmT, CU_TENSOR_MAP_DATA_TYPE_BFLOAT16, 2, d_in[1], dims, st, box, es, CU_TENSOR_MAP_INTERLEAVE_NONE,
        CU_TENSOR_MAP_SWIZZLE_128B, CU_TENSOR_MAP_L2_PROMOTION_NONE, CU_TENSOR_MAP_FLOAT_OOB_FILL_NONE);
  }
  void* x0 = nullptr;
  cudaGetSymbolAddress(&x0, g_x0);
  {
    cuuint64_t dims[2] = {FS * 64, NB}, st[1] = {FS * 128};
    cuuint32_t box[2] = {64, NC_GEMM + 1};
    enc(&tmS, CU_TENSOR_MAP_DATA_TYPE_BFLOAT16, 2, x0, dims, st, box, es, CU_TENSOR_MAP_INTERLEAVE_NONE,
        CU_TENSOR_MAP_SWIZZLE_128B, CU_TENSOR_MAP_L2_PROMOTION_NONE, CU_TENSOR_MAP_FLOAT_OOB_FILL_NONE);
  }
  {
    cuuint64_t dims[2] = {64, NB * FS}, st[1] = {128};
    cuuint32_t box[2] = {64, FS};
    enc(&tmC, CU_TENSOR_MAP_DATA_TYPE_BFLOAT16, 2, x0, dims, st, box, es, CU_TENSOR_MAP_INTERLEAVE_NONE,
        CU_TENSOR_MAP_SWIZZLE_128B, CU_TENSOR_MAP_L2_PROMOTION_NONE, CU_TENSOR_MAP_FLOAT_OOB_FILL_NONE);
  }
  GPtr gp;
  gp.zero = 0;
  cudaGetSymbolAddress((void**)&gp.s, g_scratch);
  cudaGetSymbolAddress((void**)&gp.tab, g_slot_tab);
  cudaFuncSetAttribute(xdeepfm_kernel, cudaFuncAttributeMaxDynamicSharedMemorySize, SMEM_BYTES);
  xdeepfm_kernel<<<GRID, 384, SMEM_BYTES, cudaStreamPerThread>>>(
      (const int*)d_in[0], (const __nv_bfloat16*)d_in[1], (const __nv_bfloat16*)d_in[4], (const __nv_bfloat16*)d_in[5],
      (const __nv_bfloat16*)d_in[6], (const __nv_bfloat16*)d_in[2], (const __nv_bfloat16*)d_in[3],
      (const __nv_bfloat16*)d_in[7], (__nv_bfloat16*)d_out, gp, tmW, tmT, tmS, tmC);
}
```

```cpp
#include <cuda_runtime.h>
#include <cuda_bf16.h>
#include <cuda.h>
#include <stdint.h>

__device__ __forceinline__ void wgmma_ss_n256(float (&d)[96], float (&e)[32], uint64_t descA, uint64_t descB, int scaleD) {
  asm volatile("{\n.reg .pred p;\nsetp.ne.b32 p, %130, 0;\n"
      "wgmma.mma_async.sync.aligned.m64n256k16.f32.bf16.bf16 {"
      "%0, %1, %2, %3, %4, %5, %6, %7, %8, %9, %10, %11, %12, %13, %14, %15,"
      "%16, %17, %18, %19, %20, %21, %22, %23, %24, %25, %26, %27, %28, %29, %30, %31,"
      "%32, %33, %34, %35, %36, %37, %38, %39, %40, %41, %42, %43, %44, %45, %46, %47,"
      "%48, %49, %50, %51, %52, %53, %54, %55, %56, %57, %58, %59, %60, %61, %62, %63,"
      "%64, %65, %66, %67, %68, %69, %70, %71, %72, %73, %74, %75, %76, %77, %78, %79,"
      "%80, %81, %82, %83, %84, %85, %86, %87, %88, %89, %90, %91, %92, %93, %94, %95,"
      "%96, %97, %98, %99, %100, %101, %102, %103, %104, %105, %106, %107, %108, %109, %110, %111,"
      "%112, %113, %114, %115, %116, %117, %118, %119, %120, %121, %122, %123, %124, %125, %126, %127"
      "}, %128, %129, p, 1, 1, 0, 1;\n}\n"
      : "+f"(d[0]), "+f"(d[1]), "+f"(d[2]), "+f"(d[3]), "+f"(d[4]), "+f"(d[5]), "+f"(d[6]), "+f"(d[7]),
        "+f"(d[8]), "+f"(d[9]), "+f"(d[10]), "+f"(d[11]), "+f"(d[12]), "+f"(d[13]), "+f"(d[14]), "+f"(d[15]),
        "+f"(d[16]), "+f"(d[17]), "+f"(d[18]), "+f"(d[19]), "+f"(d[20]), "+f"(d[21]), "+f"(d[22]), "+f"(d[23]),
        "+f"(d[24]), "+f"(d[25]), "+f"(d[26]), "+f"(d[27]), "+f"(d[28]), "+f"(d[29]), "+f"(d[30]), "+f"(d[31]),
        "+f"(d[32]), "+f"(d[33]), "+f"(d[34]), "+f"(d[35]), "+f"(d[36]), "+f"(d[37]), "+f"(d[38]), "+f"(d[39]),
        "+f"(d[40]), "+f"(d[41]), "+f"(d[42]), "+f"(d[43]), "+f"(d[44]), "+f"(d[45]), "+f"(d[46]), "+f"(d[47]),
        "+f"(d[48]), "+f"(d[49]), "+f"(d[50]), "+f"(d[51]), "+f"(d[52]), "+f"(d[53]), "+f"(d[54]), "+f"(d[55]),
        "+f"(d[56]), "+f"(d[57]), "+f"(d[58]), "+f"(d[59]), "+f"(d[60]), "+f"(d[61]), "+f"(d[62]), "+f"(d[63]),
        "+f"(d[64]), "+f"(d[65]), "+f"(d[66]), "+f"(d[67]), "+f"(d[68]), "+f"(d[69]), "+f"(d[70]), "+f"(d[71]),
        "+f"(d[72]), "+f"(d[73]), "+f"(d[74]), "+f"(d[75]), "+f"(d[76]), "+f"(d[77]), "+f"(d[78]), "+f"(d[79]),
        "+f"(d[80]), "+f"(d[81]), "+f"(d[82]), "+f"(d[83]), "+f"(d[84]), "+f"(d[85]), "+f"(d[86]), "+f"(d[87]),
        "+f"(d[88]), "+f"(d[89]), "+f"(d[90]), "+f"(d[91]), "+f"(d[92]), "+f"(d[93]), "+f"(d[94]), "+f"(d[95]),
        "+f"(e[0]), "+f"(e[1]), "+f"(e[2]), "+f"(e[3]), "+f"(e[4]), "+f"(e[5]), "+f"(e[6]), "+f"(e[7]),
        "+f"(e[8]), "+f"(e[9]), "+f"(e[10]), "+f"(e[11]), "+f"(e[12]), "+f"(e[13]), "+f"(e[14]), "+f"(e[15]),
        "+f"(e[16]), "+f"(e[17]), "+f"(e[18]), "+f"(e[19]), "+f"(e[20]), "+f"(e[21]), "+f"(e[22]), "+f"(e[23]),
        "+f"(e[24]), "+f"(e[25]), "+f"(e[26]), "+f"(e[27]), "+f"(e[28]), "+f"(e[29]), "+f"(e[30]), "+f"(e[31])
      : "l"(descA), "l"(descB), "r"(scaleD));
}
__device__ __forceinline__ void wgmma_ss_n192(float (&d)[96], uint64_t descA, uint64_t descB, int scaleD) {
  asm volatile("{\n.reg .pred p;\nsetp.ne.b32 p, %98, 0;\n"
      "wgmma.mma_async.sync.aligned.m64n192k16.f32.bf16.bf16 {"
      "%0, %1, %2, %3, %4, %5, %6, %7, %8, %9, %10, %11, %12, %13, %14, %15,"
      "%16, %17, %18, %19, %20, %21, %22, %23, %24, %25, %26, %27, %28, %29, %30, %31,"
      "%32, %33, %34, %35, %36, %37, %38, %39, %40, %41, %42, %43, %44, %45, %46, %47,"
      "%48, %49, %50, %51, %52, %53, %54, %55, %56, %57, %58, %59, %60, %61, %62, %63,"
      "%64, %65, %66, %67, %68, %69, %70, %71, %72, %73, %74, %75, %76, %77, %78, %79,"
      "%80, %81, %82, %83, %84, %85, %86, %87, %88, %89, %90, %91, %92, %93, %94, %95"
      "}, %96, %97, p, 1, 1, 0, 1;\n}\n"
      : "+f"(d[0]), "+f"(d[1]), "+f"(d[2]), "+f"(d[3]), "+f"(d[4]), "+f"(d[5]), "+f"(d[6]), "+f"(d[7]),
        "+f"(d[8]), "+f"(d[9]), "+f"(d[10]), "+f"(d[11]), "+f"(d[12]), "+f"(d[13]), "+f"(d[14]), "+f"(d[15]),
        "+f"(d[16]), "+f"(d[17]), "+f"(d[18]), "+f"(d[19]), "+f"(d[20]), "+f"(d[21]), "+f"(d[22]), "+f"(d[23]),
        "+f"(d[24]), "+f"(d[25]), "+f"(d[26]), "+f"(d[27]), "+f"(d[28]), "+f"(d[29]), "+f"(d[30]), "+f"(d[31]),
        "+f"(d[32]), "+f"(d[33]), "+f"(d[34]), "+f"(d[35]), "+f"(d[36]), "+f"(d[37]), "+f"(d[38]), "+f"(d[39]),
        "+f"(d[40]), "+f"(d[41]), "+f"(d[42]), "+f"(d[43]), "+f"(d[44]), "+f"(d[45]), "+f"(d[46]), "+f"(d[47]),
        "+f"(d[48]), "+f"(d[49]), "+f"(d[50]), "+f"(d[51]), "+f"(d[52]), "+f"(d[53]), "+f"(d[54]), "+f"(d[55]),
        "+f"(d[56]), "+f"(d[57]), "+f"(d[58]), "+f"(d[59]), "+f"(d[60]), "+f"(d[61]), "+f"(d[62]), "+f"(d[63]),
        "+f"(d[64]), "+f"(d[65]), "+f"(d[66]), "+f"(d[67]), "+f"(d[68]), "+f"(d[69]), "+f"(d[70]), "+f"(d[71]),
        "+f"(d[72]), "+f"(d[73]), "+f"(d[74]), "+f"(d[75]), "+f"(d[76]), "+f"(d[77]), "+f"(d[78]), "+f"(d[79]),
        "+f"(d[80]), "+f"(d[81]), "+f"(d[82]), "+f"(d[83]), "+f"(d[84]), "+f"(d[85]), "+f"(d[86]), "+f"(d[87]),
        "+f"(d[88]), "+f"(d[89]), "+f"(d[90]), "+f"(d[91]), "+f"(d[92]), "+f"(d[93]), "+f"(d[94]), "+f"(d[95])
      : "l"(descA), "l"(descB), "r"(scaleD));
}
template <unsigned long long DESC, int SCALE>
__device__ __forceinline__ void wgmma_rs_n56(float (&d)[28], uint32_t a0, uint32_t a1, uint32_t a2, uint32_t a3) {
  asm volatile("{\n.reg .b64 desc;\nmov.b64 desc, %32;\n"
      "wgmma.mma_async.sync.aligned.m64n56k16.f32.bf16.bf16 {"
      "%0, %1, %2, %3, %4, %5, %6, %7, %8, %9, %10, %11, %12, %13, %14, %15,"
      "%16, %17, %18, %19, %20, %21, %22, %23, %24, %25, %26, %27"
      "}, {%28, %29, %30, %31}, desc, %33, 1, 1, 0;\n}\n"
      : "+f"(d[0]), "+f"(d[1]), "+f"(d[2]), "+f"(d[3]), "+f"(d[4]), "+f"(d[5]), "+f"(d[6]), "+f"(d[7]),
        "+f"(d[8]), "+f"(d[9]), "+f"(d[10]), "+f"(d[11]), "+f"(d[12]), "+f"(d[13]), "+f"(d[14]), "+f"(d[15]),
        "+f"(d[16]), "+f"(d[17]), "+f"(d[18]), "+f"(d[19]), "+f"(d[20]), "+f"(d[21]), "+f"(d[22]), "+f"(d[23]),
        "+f"(d[24]), "+f"(d[25]), "+f"(d[26]), "+f"(d[27])
      : "r"(a0), "r"(a1), "r"(a2), "r"(a3), "n"(DESC), "n"(SCALE));
}
template <unsigned long long DESC, int SCALE>
__device__ __forceinline__ void wgmma_rs_n32(float (&d)[28], uint32_t a0, uint32_t a1, uint32_t a2, uint32_t a3) {
  asm volatile("{\n.reg .b64 desc;\nmov.b64 desc, %20;\n"
      "wgmma.mma_async.sync.aligned.m64n32k16.f32.bf16.bf16 {"
      "%0, %1, %2, %3, %4, %5, %6, %7, %8, %9, %10, %11, %12, %13, %14, %15"
      "}, {%16, %17, %18, %19}, desc, %21, 1, 1, 0;\n}\n"
      : "+f"(d[0]), "+f"(d[1]), "+f"(d[2]), "+f"(d[3]), "+f"(d[4]), "+f"(d[5]), "+f"(d[6]), "+f"(d[7]),
        "+f"(d[8]), "+f"(d[9]), "+f"(d[10]), "+f"(d[11]), "+f"(d[12]), "+f"(d[13]), "+f"(d[14]), "+f"(d[15])
      : "r"(a0), "r"(a1), "r"(a2), "r"(a3), "n"(DESC), "n"(SCALE));
}

constexpr int NB = 4096, NF = 26, DIN = 1664;
constexpr int NGEMM = 128, NEXTRA = 4, GRID = NGEMM + NEXTRA;
constexpr int NC_EXTRA = 80;
constexpr int NC_WG0 = 16;
constexpr int HK = 4;
constexpr int PE0 = 9;
constexpr int WD = 2;
constexpr int GI = 3;
constexpr int PE1 = 4;
constexpr int PE2 = 8;
constexpr int PS2 = 6;
constexpr int POLL = 400;
constexpr int BGN = 1;
constexpr int XD = 1000;
constexpr int PREG = 40;
constexpr int PS = 6;
constexpr int RB = 4;
constexpr int NC_GEMM = 29, NBIG = NB - NGEMM * NC_GEMM - NEXTRA * NC_EXTRA;
static_assert(NBIG >= 0 && NBIG <= NGEMM && NC_EXTRA % 4 == 0 && NC_EXTRA <= 96, "split");
constexpr int CW_MAIN = 22 * 1792, CW_LIN = 2 * 1024, CW_BYTES = CW_MAIN + CW_LIN;
constexpr int XSLOT = 4096;

constexpr int UNIT = 8192, FS = 18;
constexpr int U_W = 6, U_XB = 18, U_SP = 24;
constexpr int CW_CUT = 9;
constexpr int OFF_CW = 0, OFF_CW2 = 6 * UNIT, OFF_CWL = 9 * UNIT;
constexpr int CROW = 528;
constexpr int OFF_PARK = 10 * UNIT, OFF_PARK2 = 24 * UNIT;
constexpr int OFF_RS0 = OFF_CWL + CW_LIN, OFF_RS1 = OFF_CWL - 1024;
constexpr int OFF_GIDX = 26 * UNIT;
constexpr int OFF_TIDX = OFF_GIDX + 128 * NF * 4 - 8 * 64 * 4;
constexpr int OFF_CIDX = OFF_GIDX + 128 * NF * 4;
constexpr int OFF_EPI = OFF_CIDX + 32 * 8 * 4;
constexpr int OFF_DNN = OFF_EPI + 128 * 16;
constexpr int OFF_BAR = OFF_DNN + 112 * 8;
constexpr int SMEM_BYTES = OFF_BAR + 50 * 8;
static_assert(CW_CUT * 1792 <= 2 * UNIT && (22 - CW_CUT) * 1792 <= 3 * UNIT , "smem");
constexpr uint32_t SMEM_BASE = 1024;
static_assert(SMEM_BYTES <= 232448, "smem");
static_assert(OFF_EPI % 16 == 0 && OFF_BAR % 8 == 0, "align");
constexpr int XOFF_W3 = 0, XOFF_W2 = 35152, XOFF_W1 = 70304, XOFF_M = XOFF_W1 + 8 * 1352, XOFF_S = XOFF_M + 32 * 40 * 4,
              XOFF_SLOT = 10 * UNIT, XOFF_CIN0 = 2 * UNIT, XOFF_CIN1 = 18 * UNIT, XOFF_CIDX = 22 * UNIT,
              XOFF_BAR = 24 * UNIT, NPAIR = NC_EXTRA / 4;
static_assert(XOFF_S + 14 * 3136 <= 21 * UNIT && 48 * CROW <= 4 * UNIT, "smem");

constexpr int BAR_PARK = 7,
              BAR_FULL = 8,
              BAR_EV = 16,
              BAR_CW = 24,
              BAR_GIDX = 25,
              BAR_X0 = 26,
              BAR_W0 = 27,
              BAR_DNN = 28,
              BAR_T = 29,
              BAR_GDONE = 30,
              BAR_EPOCH = 31,
              BAR_CFULL = 32,
              BAR_C0 = 48;
constexpr int EV_CW = 29, EV_SLOT = 30, EV_END = 33;
__device__ __forceinline__ uint32_t ev_bar(uint32_t bars, int e) { return bars + 8 * (BAR_EV + (e & 7)); }
__device__ __forceinline__ uint32_t ev_par(int e) { return (e >> 3) & 1; }
constexpr unsigned long long STAGES = 0xb4b4924924924ull;
__host__ __device__ constexpr int b_x(int t) { return ((0xb2c1430bu >> (4 * t)) & 15) * 2; }
__host__ __device__ constexpr int b_w(int t) { return (0x0d0a120eu >> (8 * (t & 3))) & 31; }
__host__ __device__ constexpr int b_ws(int t) { return (t & 3) == 3 ? 4 : 1; }

struct Scratch {
  uint4 cw[CW_BYTES / 16];
  uint2 part[8 * NB];
  unsigned epoch[GRID];
  unsigned foldflag;
};
__device__ __align__(128) Scratch g_scratch;
__device__ __align__(1024) __nv_bfloat16 g_x0[NB * FS * 64];
struct GPtr { Scratch* s; const uint4* tab; uint32_t zero; };

__device__ __forceinline__ void wg_fence() { asm volatile("wgmma.fence.sync.aligned;" ::: "memory"); }
__device__ __forceinline__ void wg_commit() { asm volatile("wgmma.commit_group.sync.aligned;" ::: "memory"); }
template <int N> __device__ __forceinline__ void wg_wait() { asm volatile("wgmma.wait_group.sync.aligned %0;" ::"n"(N) : "memory"); }
__device__ __forceinline__ uint64_t mkdesc(uint32_t addr, uint32_t lbo, uint32_t sbo, uint32_t swz) {
  return (uint64_t)((addr & 0x3FFFF) >> 4) | ((uint64_t)(lbo >> 4) << 16) | ((uint64_t)(sbo >> 4) << 32) | ((uint64_t)swz << 62);
}
__device__ __forceinline__ bool elect1() {
  uint32_t p; asm volatile("{\n.reg .pred p;\nelect.sync _|p, 0xffffffff;\nselp.b32 %0, 1, 0, p;\n}" : "=r"(p)); return p;
}
__device__ __forceinline__ int fresh(int v) { asm volatile("" : "+r"(v)); return v; }
__device__ __forceinline__ void mbar_init(uint32_t bar, uint32_t cnt) { asm volatile("mbarrier.init.shared::cta.b64 [%0], %1;" ::"r"(bar), "r"(cnt) : "memory"); }
__device__ __forceinline__ void mbar_arrive(uint32_t bar) { asm volatile("mbarrier.arrive.shared::cta.b64 _, [%0];" ::"r"(bar) : "memory"); }
__device__ __forceinline__ void mbar_arrive_cta(uint32_t bar, uint32_t cta) {
  asm volatile("{\n.reg .b32 r;\nmapa.shared::cluster.u32 r, %0, %1;\nmbarrier.arrive.shared::cluster.b64 _, [r];\n}" ::"r"(bar), "r"(cta) : "memory");
}
__device__ __forceinline__ void mbar_expect_tx(uint32_t bar, uint32_t bytes) { asm volatile("mbarrier.arrive.expect_tx.shared::cta.b64 _, [%0], %1;" ::"r"(bar), "r"(bytes) : "memory"); }
__device__ __forceinline__ void mbar_wait(uint32_t bar, uint32_t parity) {
  asm volatile("{\n.reg .pred p;\nLAB_WAIT:\n"
               "mbarrier.try_wait.parity.shared::cta.b64 p, [%0], %1;\n"
               "@!p bra LAB_WAIT;\n}" ::"r"(bar), "r"(parity) : "memory");
}
__device__ __forceinline__ void flag_wait(const unsigned* p, unsigned target, unsigned sleep_ns) {
  asm volatile("{\n.reg .pred p;\n.reg .u32 n, v;\nmov.u32 n, 0;\nLAB_WAIT:\n"
               "ld.acquire.gpu.global.u32 v, [%0];\n"
               "sub.u32 v, v, %1;\n"
               "setp.ge.s32 p, v, 0;\n"
               "@p bra DONE;\n"
               "nanosleep.u32 %2;\n"
               "add.u32 n, n, 1;\n"
               "setp.lt.u32 p, n, 400000;\n"
               "@p bra LAB_WAIT;\n"
               "DONE:\n}" ::"l"(p), "r"(target), "r"(sleep_ns) : "memory");
}
__device__ __forceinline__ void put_tagged(uint2* p, float v, unsigned tag) {
  asm volatile("st.relaxed.gpu.global.v2.b32 [%0], {%1, %2};" ::"l"(p), "r"(__float_as_uint(v)), "r"(tag) : "memory");
}
__device__ __forceinline__ void flag_add(unsigned* p) { asm volatile("red.release.gpu.global.add.u32 [%0], 1;" ::"l"(p) : "memory"); }
__device__ __forceinline__ void tma_load(uint32_t dst, const CUtensorMap* tm, int c0, int c1, uint32_t bar) {
  asm volatile("cp.async.bulk.tensor.2d.shared::cluster.global.mbarrier::complete_tx::bytes [%0], [%1, {%3, %4}], [%2];"
               ::"r"(dst), "l"(tm), "r"(bar), "r"(c0), "r"(c1) : "memory");
}
__device__ __forceinline__ void tma_row_mc(uint32_t dst, const CUtensorMap* tm, int row, uint32_t bar) {
  asm volatile("cp.async.bulk.tensor.2d.shared::cluster.global.mbarrier::complete_tx::bytes.multicast::cluster [%0], [%1, {%3, %4}], [%2], %5;"
               ::"r"(dst), "l"(tm), "r"(bar), "r"(0), "r"(row), "h"((uint16_t)3));
}
__device__ __forceinline__ void tma_row(uint32_t dst, const CUtensorMap* tm, int row, uint32_t bar) {
  asm volatile("cp.async.bulk.tensor.2d.shared::cluster.global.mbarrier::complete_tx::bytes [%0], [%1, {%3, %4}], [%2];"
               ::"r"(dst), "l"(tm), "r"(bar), "r"(0), "r"(row));
}
__device__ __forceinline__ void tma_store(const CUtensorMap* tm, int c0, int c1, uint32_t src) {
  asm volatile("cp.async.bulk.tensor.2d.global.shared::cta.bulk_group [%0, {%1, %2}], [%3];\ncp.async.bulk.commit_group;"
               ::"l"(tm), "r"(c0), "r"(c1), "r"(src) : "memory");
}
template <int N> __device__ __forceinline__ void store_read() { asm volatile("cp.async.bulk.wait_group.read %0;" ::"n"(N) : "memory"); }
__device__ __forceinline__ void bulk_load(uint32_t dst, const void* src, uint32_t bytes, uint32_t bar) {
  asm volatile("cp.async.bulk.shared::cluster.global.mbarrier::complete_tx::bytes [%0], [%1], %2, [%3];"
               ::"r"(dst), "l"(src), "r"(bytes), "r"(bar));
}
__device__ __forceinline__ void l2_prefetch(const void* src, uint32_t bytes) {
  asm volatile("cp.async.bulk.prefetch.L2.global [%0], %1;" ::"l"(src), "r"(bytes));
}
__device__ __forceinline__ void w_prefetch(const __nv_bfloat16* w1, int f, int cta, int piece) {
  l2_prefetch(w1 + (f * 64 + (cta >> 3) * 4 + (cta & 1) * 2 + (piece & 1)) * DIN + (piece < 2 ? (cta & 6) * 192 : 1536 + (cta & 4) * 16),
              piece < 2 ? 768 : 128);
}
__device__ __forceinline__ void cpasync16(uint32_t dst, const void* src) {
  asm volatile("cp.async.cg.shared.global [%0], [%1], 16;" ::"r"(dst), "l"(src) : "memory");
}
template <int ID, int N> __device__ __forceinline__ void bar_sync() { asm volatile("bar.sync %0, %1;" ::"n"(ID), "n"(N) : "memory"); }
template <int ID, int N> __device__ __forceinline__ void bar_arrive() { asm volatile("bar.arrive %0, %1;" ::"n"(ID), "n"(N) : "memory"); }
__device__ __forceinline__ void ldsm4t(uint32_t& a, uint32_t& b, uint32_t& c, uint32_t& d, uint32_t addr) {
  asm volatile("ldmatrix.sync.aligned.m8n8.x4.trans.shared.b16 {%0,%1,%2,%3}, [%4];" : "=r"(a), "=r"(b), "=r"(c), "=r"(d) : "r"(addr) : "memory");
}
__device__ __forceinline__ int lds32(uint32_t addr) { int v; asm volatile("ld.shared.b32 %0, [%1];" : "=r"(v) : "r"(addr)); return v; }
__device__ __forceinline__ int2 lds64(uint32_t addr) { int2 v; asm volatile("ld.shared.v2.b32 {%0,%1}, [%2];" : "=r"(v.x), "=r"(v.y) : "r"(addr)); return v; }
__device__ __forceinline__ int4 lds128(uint32_t addr) {
  int4 v; asm volatile("ld.shared.v4.b32 {%0,%1,%2,%3}, [%4];" : "=r"(v.x), "=r"(v.y), "=r"(v.z), "=r"(v.w) : "r"(addr)); return v;
}
__device__ __forceinline__ float4 lds128f(uint32_t addr) {
  float4 v; asm volatile("ld.shared.v4.f32 {%0,%1,%2,%3}, [%4];" : "=f"(v.x), "=f"(v.y), "=f"(v.z), "=f"(v.w) : "r"(addr) : "memory"); return v;
}
__device__ __forceinline__ float4 lds128f(uint32_t addr, uint32_t off) {
  float4 v;
  asm volatile("{\n.reg .u32 t;\nadd.u32 t, %4, %5;\nld.shared.v4.f32 {%0,%1,%2,%3}, [t];\n}" : "=f"(v.x), "=f"(v.y), "=f"(v.z), "=f"(v.w) : "r"(addr), "r"(off) : "memory");
  return v;
}
__device__ __forceinline__ void sts32f(uint32_t addr, float v) { asm volatile("st.shared.f32 [%0], %1;" ::"r"(addr), "f"(v) : "memory"); }
__device__ __forceinline__ float bf_lo(uint32_t v) { return __uint_as_float(v << 16); }
__device__ __forceinline__ float bf_hi(uint32_t v) { return __uint_as_float(v & 0xffff0000u); }
__device__ __forceinline__ float bf2f(__nv_bfloat16 v) { return __bfloat162float(v); }

__device__ __forceinline__ uint32_t mul2(uint32_t a, uint32_t b) {
  uint32_t r; asm volatile("mul.rn.bf16x2 %0, %1, %2;" : "=r"(r) : "r"(a), "r"(b)); return r;
}
__device__ __forceinline__ uint32_t mul2lo(uint32_t a, uint32_t b) {
  uint32_t r;
  asm volatile("{\n.reg .b16 l, h;\n.reg .b32 t;\nmov.b32 {l, h}, %2;\nmov.b32 t, {l, l};\nmul.rn.bf16x2 %0, %1, t;\n}" : "=r"(r) : "r"(a), "r"(b));
  return r;
}
__device__ __forceinline__ uint32_t mul2hi(uint32_t a, uint32_t b) {
  uint32_t r;
  asm volatile("{\n.reg .b16 l, h;\n.reg .b32 t;\nmov.b32 {l, h}, %2;\nmov.b32 t, {h, h};\nmul.rn.bf16x2 %0, %1, t;\n}" : "=r"(r) : "r"(a), "r"(b));
  return r;
}

__host__ __device__ constexpr int xfield(int r, int e, int c) {
  return r == 9 ? 24 + e : 8 * (r / 3) + 2 * (((r % 3) + c) & 3) + (((r % 3) == 2 && c >= 2) ? 1 - e : e);
}
__host__ __device__ constexpr int blk_a(int b) { return b < 12 ? 3 * (b / 8) + ((b & 3) == 3) : (b < 15 ? 3 * (b - 12) : 3 * (b - 15)); }
__host__ __device__ constexpr int blk_b(int b) { return b < 12 ? 3 * (b < 4 ? 1 : 2) + ((b & 3) == 3 ? 0 : (b & 3)) : (b < 15 ? 3 * (b - 12) + 1 : 9); }
__host__ __device__ constexpr int slot_pq(int u, int e, int c) {
  return u < 36 ? (xfield(blk_a(u >> 1), e, c) | (xfield(blk_b(u >> 1), u & 1, c) << 8))
       : u < 39 ? (xfield(3 * (u - 36), e, c) * 257)
       : u < 42 ? (xfield(3 * (u - 39), e, c) | (xfield(3 * (u - 39) + 2, e, c) << 8))
       : u == 42 ? (xfield(3 * e, 0, c) | (xfield(3 * e, 1, c) << 8))
       : u == 43 ? (e == 0 ? (xfield(6, 0, c) | (xfield(6, 1, c) << 8))
                           : (c == 0 ? 24 * 257 : c == 1 ? 25 * 257 : c == 2 ? (24 | 25 << 8) : 26 * 257))
       : u < 47 ? (xfield(3 * (u - 44), e, c) | (26 << 8))
       : (c == 0 ? ((24 + e) | 26 << 8) : 27 * 257);
}
struct SlotTab { uint32_t v[48 * 8]; };
constexpr SlotTab make_slot_tab() {
  SlotTab t{};
  for (int u = 0; u < 48; u++)
    for (int k = 0; k < 8; k++) {
      const int pq = slot_pq(u, k & 1, k >> 1), p = pq & 255, q = pq >> 8;
      t.v[u * 8 + k] = (uint32_t)((p * 28 + q) * 4) | ((uint32_t)(((p != q && q < 26) ? q * 28 + p : 27 * 28 + 27) * 4) << 16);
    }
  return t;
}
__device__ __align__(16) const SlotTab g_slot_tab = make_slot_tab();

struct CinCtx {
  uint32_t o03, o14, o25, o69, o78, cin, selA, selB;
  bool ones, lead;
  uint32_t so, so2, co, co2, bar, jump, dslot, last;
  bool ring;
};
constexpr unsigned long long CW_DESC = (unsigned long long)((SMEM_BASE + OFF_CW) >> 4) | (8ull << 16) | (16ull << 32);
constexpr unsigned long long CWL_DESC = CW_DESC + (OFF_CWL - OFF_CW) / 16;

template <int U>
__device__ __forceinline__ uint32_t zreg(const uint32_t (&x)[10][2], int h, const CinCtx& c) {
  if constexpr (U < 36) {
    if constexpr (U & 1) return mul2hi(x[blk_a(U >> 1)][h], x[blk_b(U >> 1)][h]);
    else return mul2lo(x[blk_a(U >> 1)][h], x[blk_b(U >> 1)][h]);
  } else if constexpr (U < 39) {
    return mul2(x[3 * (U - 36)][h], x[3 * (U - 36)][h]);
  } else if constexpr (U < 42) {
    return mul2(x[3 * (U - 39)][h], x[3 * (U - 39) + 2][h]);
  } else if constexpr (U == 42) {
    return mul2(__byte_perm(x[0][h], x[3][h], 0x5410), __byte_perm(x[0][h], x[3][h], 0x7632));
  } else {
    const uint32_t f = c.ones ? 0x3f803f80u : x[9][h];
    return mul2(__byte_perm(x[6][h], f, c.selA), __byte_perm(x[6][h], f, c.selB));
  }
}

template <int G>
__device__ __forceinline__ void z_fill(uint32_t (&z)[8], const uint32_t (&x)[10][2], const CinCtx& c) {
  z[0] = zreg<4 * G>(x, 0, c);     z[1] = zreg<4 * G>(x, 1, c);
  z[2] = zreg<4 * G + 1>(x, 0, c); z[3] = zreg<4 * G + 1>(x, 1, c);
  z[4] = zreg<4 * G + 2>(x, 0, c); z[5] = zreg<4 * G + 2>(x, 1, c);
  z[6] = zreg<4 * G + 3>(x, 0, c); z[7] = zreg<4 * G + 3>(x, 1, c);
}
__host__ __device__ constexpr unsigned long long cw_desc(int s) { return CW_DESC + (s < CW_CUT ? s * 1792 : OFF_CW2 - OFF_CW + (s - CW_CUT) * 1792) / 16; }
template <int G>
__device__ __forceinline__ void z_mma(float (&acc)[28], const uint32_t (&z)[8]) {
  wgmma_rs_n56<cw_desc(2 * G), G != 0>(acc, z[0], z[1], z[2], z[3]);
  wgmma_rs_n56<cw_desc(2 * G + 1), 1>(acc, z[4], z[5], z[6], z[7]);
}

__device__ __forceinline__ void cin_finish(const CinCtx& c, float (&acc)[28], uint32_t out) {
#pragma unroll
  for (int i = 0; i < 28; i++) asm volatile("" : "+f"(acc[i]));
  float s0 = acc[12] * acc[13], s1 = acc[14] * acc[15];
#pragma unroll
  for (int i = 0; i < 12; i += 2) {
    s0 = fmaf(acc[i], acc[16 + i], s0);
    s1 = fmaf(acc[i + 1], acc[17 + i], s1);
  }
  sts32f(c.cin + out, s0 + s1);
}

__device__ __forceinline__ void cin_ldsm(const CinCtx& c, uint32_t so, uint32_t (&x)[10][2]) {
  ldsm4t(x[0][0], x[0][1], x[3][0], x[3][1], so + c.o03);
  ldsm4t(x[1][0], x[1][1], x[4][0], x[4][1], so + c.o14);
  ldsm4t(x[2][0], x[2][1], x[5][0], x[5][1], so + c.o25);
  ldsm4t(x[6][0], x[6][1], x[9][0], x[9][1], so + c.o69);
  ldsm4t(x[7][0], x[7][1], x[8][0], x[8][1], so + c.o78);
}
__device__ __forceinline__ void cin_load(const CinCtx& c, int k, bool real, uint32_t (&x)[10][2]) {
  if (k == 0 && real) mbar_wait(c.bar, 0);
  cin_ldsm(c, k ? c.so2 : c.so, x);
  if (k == 1 && c.lead) mbar_arrive(c.bar + 8 * NPAIR);
}
__device__ __forceinline__ void cin_advance(CinCtx& c) {
  const uint32_t d = c.so == c.jump ? c.dslot : 2 * XSLOT;
  c.so += d; c.so2 += d;
  c.co = c.ring ? c.co + 2 * CROW : c.so;
  c.bar += 8;
}
constexpr int CG_WAIT = 3;
constexpr int CG_FIN = 3;
constexpr int CG_HEAD = 4;
constexpr int CG_LIN = 5;
constexpr int CG_LOAD = 5;
constexpr int CG_N = 11;
static_assert(CG_FIN >= CG_WAIT && CG_FIN < CG_HEAD && CG_LOAD >= CG_HEAD && CG_LIN >= CG_HEAD && CG_LOAD < 10, "CIN schedule");
template <int G, int GEND, typename F>
__device__ __forceinline__ void cin_groups(const CinCtx& c, const uint32_t (&x)[10][2], float (&acc)[28], uint32_t (&z)[8],
                                           int q, bool more, uint32_t (&xn)[10][2], F finish) {
  if constexpr (G < GEND) {
    wg_fence();
    if constexpr (G == CG_LIN) {
      wgmma_rs_n32<CWL_DESC, 1>(acc, x[0][0], x[0][1], x[3][0], x[3][1]);
      wgmma_rs_n32<CWL_DESC + 1024 / 16, 1>(acc, x[6][0], x[6][1], x[9][0], x[9][1]);
    }
    z_mma<G>(acc, z);
    wg_commit();
    if constexpr (G == CG_LOAD) cin_load(c, q, more, xn);
    uint32_t zn[8];
    if constexpr (G + 1 < CG_N) z_fill<G + 1>(zn, x, c); else z_fill<0>(zn, xn, c);
    if constexpr (G == CG_FIN) finish();
    wg_wait<CG_WAIT>();
    if constexpr (G + 1 < GEND) cin_groups<G + 1, GEND>(c, x, acc, zn, q, more, xn, finish);
    else {
#pragma unroll
      for (int i = 0; i < 8; i++) z[i] = zn[i];
    }
    if constexpr (G + 1 < GEND) {
#pragma unroll
      for (int i = 0; i < 8; i++) z[i] = zn[i];
    }
  }
}
template <typename F>
__device__ __forceinline__ void cin_head(const CinCtx& c, uint32_t (&x)[10][2], float (&acc)[28], uint32_t (&z)[8], F finish) {
  cin_groups<0, CG_HEAD>(c, x, acc, z, 0, false, x, finish);
}
__device__ __forceinline__ void cin_tail(const CinCtx& c, const uint32_t (&x)[10][2], float (&acc)[28], uint32_t (&z)[8],
                                         int q, bool more, uint32_t (&xn)[10][2]) {
  cin_groups<CG_HEAD, CG_N>(c, x, acc, z, q, more, xn, []() {});
}

__device__ __forceinline__ int slot_of(int wg, int j) {
  return wg ? (j == 0 ? 9 * UNIT + XSLOT : j <= 8 ? 2 * UNIT + (j - 1) * XSLOT : 21 * UNIT + (j - 9) * XSLOT)
            : (j < 3 ? OFF_GIDX + j * XSLOT : 14 * UNIT + (j - 3) * XSLOT);
}

__device__ __forceinline__ void cin_begin(CinCtx& c, uint32_t sb, int wg, uint32_t first, uint32_t (&x)[10][2], float (&acc)[28], uint32_t (&z)[8]) {
  int t; asm volatile("mov.u32 %0, %%tid.x;" : "=r"(t));
  const int m = t & 16, f0 = t & 7, f1 = (f0 + 2) & 7, f2 = (f0 ^ 4) ^ (f0 >> 2);
  const uint32_t base = sb + m * 64, ch = (t & 96) + (t & 8) * 2;
  c.o03 = (base + f0 * 0x90) ^ ch;
  c.o14 = (base + f1 * 0x90) ^ ch;
  c.o25 = (base + f2 * 0x90) ^ ch;
  c.o69 = (base + 2048 + (m ? f0 & 1 : f0) * 0x90) ^ ch;
  c.o78 = m ? c.o25 + 1024 : c.o14 + 2048;
  mbar_wait(sb + OFF_BAR + 8 * BAR_GDONE, 0);
  mbar_wait(sb + OFF_BAR + 8 * (BAR_C0 + wg), 0);
  cin_ldsm(c, first, x);
  mbar_wait(sb + OFF_BAR + 8 * BAR_CW, 0);
  z_fill<0>(z, x, c);
  cin_head(c, x, acc, z, []() {});
}
__device__ __forceinline__ void cin_setup(CinCtx& c, uint32_t sb, int wg, int p, bool gemm, int nj, uint32_t zero) {
  c.bar = sb + (gemm ? OFF_BAR + 8 * (BAR_CFULL + wg * 8) : XOFF_BAR + wg * 16 * NPAIR);
  c.lead = (p & 31) == 0 && !gemm; c.ring = !gemm;
  c.so = !gemm ? XOFF_SLOT + 8 * wg * XSLOT : wg ? 2 * UNIT : OFF_GIDX + XSLOT;
  c.jump = c.so + (gemm && !wg ? 0 : 6 * XSLOT);
  c.dslot = !gemm ? -6 * XSLOT : wg ? 19 * UNIT - 6 * XSLOT : 14 * UNIT - OFF_GIDX - XSLOT;
  c.co = gemm ? c.so : (wg ? XOFF_CIN1 : XOFF_CIN0) - NF * 128;
  c.co2 = gemm ? XSLOT : CROW;
  c.so2 = c.so + XSLOT + zero;
  c.last = gemm ? slot_of(wg, (nj - 1) | 1) : c.co + ((nj - 1) & ~1) * CROW;
  c.cin = sb + NF * 128 + p * 4;
  const int q = p & 3;
  c.selA = q == 1 ? 0x7610 : 0x5410;
  c.selB = q == 0 ? 0x5432 : 0x7632;
  c.ones = q == 3;
}
template <typename F2, typename F3>
__device__ __forceinline__ void cin_run(CinCtx& c, int nj, uint32_t (&xA)[10][2], float (&accA)[28], uint32_t (&z)[8], F2 before_end, F3 st5) {
  float accB[28];
  uint32_t xB[10][2];
  const uint32_t lastA = nj & 1 ? c.last : 0;
#pragma unroll 1
  for (int j = 0;; j += 2) {
    cin_tail(c, xA, accA, z, 0, c.co != lastA, xB);
    if (c.co == lastA) { before_end(); wg_wait<0>(); cin_finish(c, accA, c.co); break; }
    cin_head(c, xB, accB, z, [&]() { st5(j); cin_finish(c, accA, c.co); });
    cin_tail(c, xB, accB, z, 1, true, xA);
    if (c.co == c.last) { before_end(); wg_wait<0>(); cin_finish(c, accB, c.co + c.co2); break; }
    cin_head(c, xA, accA, z, [&]() { st5(j + 1); cin_finish(c, accB, c.co + c.co2); });
    cin_advance(c);
  }
}

constexpr float ALPHA = 0.3292034911525734f, KAPPA = 2.423681954311584f;
__device__ __forceinline__ float gelu_acc(float v, float ab, float w, float s, float alpha = ALPHA) {
  const float a = fmaf(v, alpha, ab);
  const float u = a * fmaf(a, a, KAPPA);
  float th; asm("tanh.approx.f32 %0, %1;" : "=f"(th) : "f"(u));
  return fmaf(fmaf(a, th, a), w, s);
}

constexpr int QD = 2;
template <int NG>
struct Gelu {
  float4 q[QD + 1];
  uint32_t ep;
  __device__ __forceinline__ void start(uint32_t a) {
    ep = a;
#pragma unroll
    for (int i = 0; i < QD; i++) q[i] = lds128f(ep + i * 64);
  }
  template <int I0, int I1>
  __device__ __forceinline__ void part(float (&d)[4 * NG], float& r0, float& r1, uint32_t done) {
    float alpha;
    asm volatile("{\n.reg .pred p;\nmbarrier.test_wait.parity.shared::cta.b64 p, [%1], 0;\nselp.f32 %0, %2, 0f7FC00000, p;\n}"
                 : "=f"(alpha) : "r"(done), "f"(ALPHA) : "memory");
    part<I0, I1>(d, r0, r1, alpha);
  }
  template <int I0, int I1>
  __device__ __forceinline__ void part(float (&d)[4 * NG], float& r0, float& r1, float alpha = ALPHA) {
#pragma unroll
    for (int i = I0; i < I1; i++) {
      if (i + QD < NG) q[(i + QD) % (QD + 1)] = lds128f(ep + (i + QD) * 64);
      const float4 v = q[i % (QD + 1)];
#pragma unroll
      for (int e = 0; e < 4; e++) asm volatile("" : "+f"(d[4 * i + e]));
      const float al = i < I0 + QD ? alpha : ALPHA;
      r0 = gelu_acc(d[4 * i + 0], v.x, v.z, r0, al);
      r0 = gelu_acc(d[4 * i + 1], v.y, v.w, r0, al);
      r1 = gelu_acc(d[4 * i + 2], v.x, v.z, r1, al);
      r1 = gelu_acc(d[4 * i + 3], v.y, v.w, r1, al);
    }
    asm volatile("" : "+f"(r0), "+f"(r1));
  }
};
__device__ __forceinline__ float quad_sum(float r0, float r1, float r2, float r3, int lane) {
  const bool b0 = lane & 1, b1 = lane & 2;
  const float a = (b0 ? r1 : r0) + __shfl_xor_sync(0xffffffffu, b0 ? r0 : r1, 1);
  const float b = (b0 ? r3 : r2) + __shfl_xor_sync(0xffffffffu, b0 ? r2 : r3, 1);
  return (b1 ? b : a) + __shfl_xor_sync(0xffffffffu, b1 ? a : b, 2);
}
__device__ __forceinline__ void sts128f(uint32_t addr, float a, float b, float c, float d) {
  asm volatile("st.shared.v4.f32 [%0], {%1, %2, %3, %4};" ::"r"(addr), "f"(a), "f"(b), "f"(c), "f"(d) : "memory");
}
__device__ __forceinline__ void pin(float a, float b, uint32_t addr, uint32_t zero) {
  asm volatile("{\n.reg .pred p;\nsetp.ne.u32 p, %3, 0;\n@p st.shared.v2.f32 [%0], {%1, %2};\n}" ::"r"(addr), "f"(a), "f"(b), "r"(zero) : "memory");
}
__device__ __forceinline__ void hand_on(float (&d)[96], const float (&s)[96]) {
#pragma unroll
  for (int i = 0; i < 96; i++) asm volatile("mov.b32 %0, %1;" : "=f"(d[i]) : "f"(s[i]));
}
__device__ __forceinline__ uint64_t desc_x(int u) { return mkdesc(SMEM_BASE, 16, 1024, 1) + u * (UNIT / 16); }
__device__ __forceinline__ uint64_t desc_w(int u, int stride = 1) { return mkdesc(SMEM_BASE, stride * UNIT, 1024, 1) + u * (UNIT / 16); }
__device__ __forceinline__ void tile_step(float (&d)[96], uint64_t dA, uint64_t dB) {
  wg_fence();
#pragma unroll
  for (int k = 0; k < 4; k++) wgmma_ss_n192(d, dA + 2 * k, dB + 128 * k, 1);
  wg_commit();
}
template <int K0 = 0, int K1 = 4>
__device__ __forceinline__ void wide_step(float (&d)[96], float (&e)[32], uint64_t dA, uint64_t dB) {
  wg_fence();
#pragma unroll
  for (int k = K0; k < K1; k++) wgmma_ss_n256(d, e, dA + 2 * k, dB + 128 * k, 1);
  wg_commit();
}
__device__ __forceinline__ int cin_row(int c, int j) {
  if (c >= NGEMM) {
    const int e = (c - NGEMM) * NC_EXTRA + j;
    c = e < 256 ? e >> 1 : NBIG + e - 256;
    j = e < 256 ? 30 + (e & 1) : 29;
  }
  return (c >> 3) * 256 + (c & 2) * 64 + (c & 1) * 64 + (c & 4) * 8 + j;
}
__device__ __forceinline__ int cin_count(int c) {
  return c < NGEMM ? NC_GEMM + (c < NBIG) : NC_EXTRA;
}

__device__ __forceinline__ int fold_i0(int e) { return e < 2 ? 7 * e : 2 + 6 * e; }
__device__ __forceinline__ uint32_t ldg16(const void* p) { uint16_t v; asm volatile("ld.global.nc.u16 %0, [%1];" : "=h"(v) : "l"(p)); return v; }
__device__ __forceinline__ uint4 ldg128(const void* p) {
  uint4 v; asm volatile("ld.global.nc.v4.u32 {%0,%1,%2,%3}, [%4];" : "=r"(v.x), "=r"(v.y), "=r"(v.z), "=r"(v.w) : "l"(p)); return v;
}
__device__ __forceinline__ void sts64f(uint32_t addr, float a, float b) { asm volatile("st.shared.v2.f32 [%0], {%1, %2};" ::"r"(addr), "f"(a), "f"(b) : "memory"); }
__device__ __forceinline__ float to_tf32(float v) { uint32_t r; asm("cvt.rna.tf32.f32 %0, %1;" : "=r"(r) : "f"(v)); return __uint_as_float(r); }
__device__ __forceinline__ uint4 fold_chunk(uint32_t base, const uint4 t0, const uint4 t1) {
  const uint32_t t[8] = {t0.x, t0.y, t0.z, t0.w, t1.x, t1.y, t1.z, t1.w};
  uint32_t v[4];
#pragma unroll
  for (int c = 0; c < 4; c++) {
    const float w0 = __int_as_float(lds32(base + (t[2 * c] & 0xffff))) + __int_as_float(lds32(base + (t[2 * c] >> 16)));
    const float w1 = __int_as_float(lds32(base + (t[2 * c + 1] & 0xffff))) + __int_as_float(lds32(base + (t[2 * c + 1] >> 16)));
    __nv_bfloat162 pk = __floats2bfloat162_rn(w0, w1);
    v[c] = *reinterpret_cast<uint32_t*>(&pk);
  }
  return make_uint4(v[0], v[1], v[2], v[3]);
}
__device__ __forceinline__ int cw_chunk(int u, int n) {
  return ((u < 44 ? (u >> 1) * 1792 : CW_MAIN + ((u - 44) >> 1) * 1024) + (n >> 3) * 256 + (u & 1) * 128 + (n & 7) * 16) >> 4;
}
__device__ __forceinline__ void fold_weights(uint8_t* smem, uint32_t sb, int e, const __nv_bfloat16* __restrict__ wco, const GPtr gp) {
  const int tid = threadIdx.x, lane = tid & 31, warp = tid >> 5;
  const uint32_t bars = sb + OFF_BAR;
  const int i0 = fold_i0(e), i = i0 + warp;
  const bool own = i < fold_i0(e + 1);
  const uint32_t wb16 = ldg16(wco + (lane < NF ? 26 + lane : 0)), wc16 = ldg16(wco + (lane < NF ? 52 + lane : 0));
  const uint32_t w116 = ldg16(wco + (own ? i : 0));
  const uint4* tab = gp.tab;
  const uint4 ta0 = ldg128(tab + 2 * lane), ta1 = ldg128(tab + 2 * lane + 1);
  const uint4 tb0 = ldg128(tab + 64 + 2 * (lane & 15)), tb1 = ldg128(tab + 65 + 2 * (lane & 15));
  asm volatile("barrier.cluster.arrive.relaxed.aligned;\nbarrier.cluster.wait.acquire.aligned;" ::: "memory");
  if (warp >= 6) {
    for (int t = tid - 192; t < 6 * 20; t += 64) sts64f(sb + XOFF_M + 26 * 160 + t * 8, 0.f, 0.f);
    if (warp == 6 && lane < NF) {
      sts64f(sb + XOFF_M + lane * 160 + 104, bf_lo(wb16), 0.f);
      sts64f(sb + XOFF_M + lane * 160 + 112, 0.f, 0.f);
      sts64f(sb + XOFF_M + lane * 160 + 120, 0.f, 0.f);
    }
    if (warp == 7) {
      gp.s->cw[cw_chunk(lane, 28 + e)] = make_uint4(0, 0, 0, 0);
      if (lane < 16) gp.s->cw[cw_chunk(32 + lane, 28 + e)] = make_uint4(0, 0, 0, 0);
    }
  } else {
    mbar_wait(bars + 8 * BAR_GIDX, 0);
    float m0 = 0.f, m1 = 0.f, m2 = 0.f, m3 = 0.f;
    const uint32_t a = sb + XOFF_W3 + (tid < 169 ? tid : 0) * 8;
#pragma unroll 2
    for (int g = 0; g < NF; g++) {
      const int2 v = lds64(a + g * 1352);
      const float w = __shfl_sync(0xffffffffu, bf_lo(wc16), g);
      m0 = fmaf(w, bf_lo(v.x), m0); m1 = fmaf(w, bf_hi(v.x), m1);
      m2 = fmaf(w, bf_lo(v.y), m2); m3 = fmaf(w, bf_hi(v.y), m3);
    }
    if (tid < 169) {
      const int o = tid * 2, o2 = o + 1;
      sts64f(sb + XOFF_M + (o / 13) * 160 + (o % 13) * 8, to_tf32(m0), to_tf32(m1));
      sts64f(sb + XOFF_M + (o2 / 13) * 160 + (o2 % 13) * 8, to_tf32(m2), to_tf32(m3));
    }
  }
  const uint32_t sT = sb + XOFF_S + warp * 2 * 3136, sA = sT + 3136;
  const int g = lane >> 2, c = lane & 3;
  uint32_t af[2][8];
  mbar_wait(bars + 8 * BAR_FULL, 0);
  if (own) {
#pragma unroll
    for (int k = 0; k < 8; k++) {
      const int h = 4 * k + c;
      const uint32_t a = sb + XOFF_W2 + ((h < NF ? h : 0) * 676 + i * 26 + 2 * g) * 2;
      af[0][k] = lds32(a);
      af[1][k] = lds32(a + (g < 5 ? 32 : 0));
    }
#pragma unroll 1
    for (int o = lane; o < 338; o += 32) {
      const uint32_t v = lds32(sb + XOFF_W1 + (i - (i0 & ~1)) * 1352 + o * 4);
      sts64f(sA + (o / 13) * 112 + (o % 13) * 8, bf_lo(v), bf_hi(v));
    }
    if (lane < 28) sts64f(sA + lane * 112 + 104, 0.f, 0.f);
    if (lane < 2) sts64f(sT + (26 + lane) * 112 + 104, lane == 0 ? bf_lo(w116) : 0.f, 0.f);
  }
  bar_sync<4, 256>();
  if (own) {
#pragma unroll 1
    for (int n = 0; n < 4; n++) {
      float d[2][4] = {};
#pragma unroll
      for (int ks = 0; ks < 4; ks++) {
        const uint32_t b0 = lds32(sb + XOFF_M + (8 * ks + c) * 160 + (8 * n + g) * 4);
        const uint32_t b1 = lds32(sb + XOFF_M + (8 * ks + c + 4) * 160 + (8 * n + g) * 4);
#pragma unroll
        for (int m = 0; m < 2; m++)
          asm volatile("mma.sync.aligned.m16n8k8.row.col.f32.tf32.tf32.f32 {%0,%1,%2,%3}, {%4,%5,%6,%7}, {%8,%9}, {%0,%1,%2,%3};"
                       : "+f"(d[m][0]), "+f"(d[m][1]), "+f"(d[m][2]), "+f"(d[m][3])
                       : "r"(af[m][2 * ks] << 16), "r"(af[m][2 * ks] & 0xffff0000u), "r"(af[m][2 * ks + 1] << 16),
                         "r"(af[m][2 * ks + 1] & 0xffff0000u), "r"(b0), "r"(b1));
      }
      if (n < 3 || c < 2) {
        const uint32_t a = sT + 2 * g * 112 + (8 * n + 2 * c) * 4;
        sts64f(a, d[0][0], d[0][1]);
        sts64f(a + 112, d[0][2], d[0][3]);
        if (g < 5) {
          sts64f(a + 16 * 112, d[1][0], d[1][1]);
          sts64f(a + 17 * 112, d[1][2], d[1][3]);
        }
      }
    }
    __syncwarp();
    const int nt = i < 24 ? i : 2 * i - 24, na = i < 24 ? 32 + i : 2 * i - 23;
#pragma unroll 1
    for (int k = 0; k < 3; k++) {
      const bool isa = k == 1 || (k == 2 && lane >= 16);
      const uint4 v = fold_chunk(isa ? sA : sT, k < 2 ? ta0 : tb0, k < 2 ? ta1 : tb1);
      if (k < 2 || lane < 28 || na < 32) gp.s->cw[cw_chunk(k < 2 ? lane : 32 + (lane & 15), isa ? na : nt)] = v;
    }
  }
  __syncwarp();
  if (lane == 0) flag_add(&gp.s->foldflag);
  bar_sync<4, 256>();
  mbar_wait(bars + 8 * BAR_GDONE, 0);
  if (tid >= 128 && tid < 132) mbar_arrive(ev_bar(bars, EV_END));
}

__global__ void __cluster_dims__(2, 1, 1) __launch_bounds__(384, 1)
xdeepfm_kernel(const int* __restrict__ idx, const __nv_bfloat16* __restrict__ table, const __nv_bfloat16* __restrict__ w1,
               const __nv_bfloat16* __restrict__ b1, const __nv_bfloat16* __restrict__ w2,
               const __nv_bfloat16* __restrict__ ws, const __nv_bfloat16* __restrict__ wco,
               const __nv_bfloat16* __restrict__ bout, __nv_bfloat16* __restrict__ out, const GPtr gp,
               const __grid_constant__ CUtensorMap tmW, const __grid_constant__ CUtensorMap tmT,
               const __grid_constant__ CUtensorMap tmS, const __grid_constant__ CUtensorMap tmC) {
  int myidx, idx1, idx2 = 0, idx3 = 0;
  {
    const int t = threadIdx.x, b = blockIdx.x, half = (b >> 1) ^ (t >= 256 ? t >> 4 : 0);
    const int* ip = idx + (((b >> 3) & 15) * 256 + (half & 1) * 128 + (t < 256 ? t >> 1 : (b & 1) * 64 + ((t >> 1) & 48) + (t & 15))) * NF;
    asm volatile("{\n.reg .pred p;\nsetp.ge.u32 p, %5, 256;\nld.global.nc.v2.s32 {%0, %1}, [%4];\n@p ld.global.nc.v2.s32 {%2, %3}, [%4 + 8];\n}"
                 : "=r"(myidx), "=r"(idx1), "+r"(idx2), "+r"(idx3) : "l"(ip), "r"(t));
  }
  extern __shared__ __align__(1024) uint8_t smem[];
  const uint32_t sb = (uint32_t)__cvta_generic_to_shared(smem);
  const uint32_t bars = sb + OFF_BAR;
  const int tid = threadIdx.x, lane = tid & 31;
  const int warp = __shfl_sync(0xffffffffu, tid >> 5, 0);
  const int cta = blockIdx.x;
  const bool gemm = cta < NGEMM;
  const int nt = cta & 7, rank = cta & 1;

  if (warp == 8 && elect1()) {
    mbar_init(bars + 8 * BAR_GIDX, 1);
    mbar_init(bars + 8 * BAR_FULL, 1);
    mbar_init(bars + 8 * BAR_W0, 1);
    asm volatile("fence.mbarrier_init.release.cluster;" ::: "memory");
    if (gemm) {
      mbar_expect_tx(bars + 8 * BAR_W0, 4 * UNIT);
#pragma unroll
      for (int i = 0; i < 4; i++)
        tma_load(sb + (U_W + i) * UNIT, &tmW, i < 3 ? nt * 192 + i * 64 : 1536 + (nt >> 2) * 64, 0, bars + 8 * BAR_W0);
      mbar_expect_tx(bars + 8 * BAR_FULL, 2 * UNIT);
    } else {
      const int i0 = fold_i0(cta - NGEMM) & ~1, ni = NF - i0 < 8 ? NF - i0 : 8;
      __nanosleep(XD);
      mbar_expect_tx(bars + 8 * BAR_GIDX, 35152);
      bulk_load(sb + XOFF_W3, ws + 2 * 17576, 35152, bars + 8 * BAR_GIDX);
      mbar_expect_tx(bars + 8 * BAR_FULL, 35152 + ni * 1352);
      bulk_load(sb + XOFF_W1, ws + i0 * 676, ni * 1352, bars + 8 * BAR_FULL);
      bulk_load(sb + XOFF_W2, ws + 17576, 35152, bars + 8 * BAR_FULL);
    }
  }
  if (warp == 7 && lane >= 16 && (lane & 7) < 7) {
    const int l = lane & 7;
    asm volatile("prefetch.global.L2 [%0];" ::"l"(w1 + (((cta >> 3 & 15) * 2 + (cta & 1)) * 2 + ((lane >> 3) & 1)) * DIN + (l < 6 ? (cta & 6) * 192 + l * 64 : 1536 + (cta & 4) * 16)));
  }

  if (warp >= 8) {
    const int pw = warp - 8;
    if (pw && elect1()) {
      if (pw == 1) {
        asm volatile("prefetch.tensormap [%0];" ::"l"(&tmT) : "memory");
#pragma unroll
        for (int i = 1; i < 8; i++) mbar_init(bars + 8 * (BAR_FULL + i), 1);
        mbar_init(bars + 8 * BAR_CW, 1);
        mbar_init(bars + 8 * BAR_X0, 1);
        mbar_init(bars + 8 * BAR_C0, 1);
        mbar_init(bars + 8 * (BAR_C0 + 1), 1);
        mbar_init(bars + 8 * BAR_T, 2);
        mbar_init(bars + 8 * BAR_PARK, 8);
      } else if (pw == 2) {
#pragma unroll
        for (int i = 0; i < 8; i++) mbar_init(bars + 8 * (BAR_EV + i), 4);
        mbar_init(bars + 8 * BAR_GDONE, 4);
        mbar_init(bars + 8 * BAR_DNN, gemm ? 1 : 4);
      } else {
#pragma unroll
        for (int i = 0; i < 16; i++) mbar_init(bars + 8 * (BAR_CFULL + i), 1);
      }
      asm volatile("fence.mbarrier_init.release.cluster;" ::: "memory");
    }
    __syncwarp();
    asm volatile("barrier.cluster.arrive.relaxed.aligned;" ::: "memory");
    asm volatile("barrier.cluster.wait.acquire.aligned;" ::: "memory");
    asm volatile("setmaxnreg.dec.sync.aligned.u32 24;");
    if (gemm) {
      {
        const uint32_t a = sb + OFF_GIDX + ((lane >> 4) * 64 + pw * 16 + (lane & 15)) * NF * 4;
        asm volatile("st.shared.v2.b32 [%0], {%1, %2};\nst.shared.v2.b32 [%0 + 8], {%3, %4};"
                     ::"r"(a), "r"(myidx), "r"(idx1), "r"(idx2), "r"(idx3) : "memory");
        __syncwarp();
      }
      if (elect1()) {
#pragma unroll
        for (int j = 0; j < 16; j += 8) {
          int r[8];
#pragma unroll
          for (int i = 0; i < 8; i++) r[i] = lds32(sb + OFF_GIDX + ((64 + pw * 16 + j + i) * NF) * 4);
#pragma unroll
          for (int i = 0; i < 8; i++) tma_row_mc(sb + U_XB * UNIT + (rank * 64 + pw * 16 + j + i) * 128, &tmT, r[i], bars + 8 * BAR_FULL);
        }
        if (pw == 0) asm volatile("prefetch.tensormap [%0];" ::"l"(&tmS) : "memory");
        int s = 1;
#pragma unroll 1
        for (int fi = 1; fi < NF; fi++) {
          const int f = fresh(fi), pw = fresh(warp) - 8, ct = fresh(cta), nt = ct & 7;
          const int t = f - FS, st = t < 0 ? s : (t & 3) ^ ((t >> 1) & 1), e = f - 3 - (t > 1);
          const uint32_t fb = bars + 8 * (BAR_FULL + (f & 7)), ia = sb + OFF_GIDX + (pw * 16 * NF + f) * 4;
          const uint32_t d = sb + (st == 3 ? U_SP : 2 * st) * UNIT + ((ct & 1) * 64 + pw * 16) * 128;
          if (f == 4) mbar_wait(bars + 8 * BAR_GIDX, 0);
          int r[2][RB];
#pragma unroll
          for (int i = 0; i < RB; i++) r[0][i] = lds32(ia + i * NF * 4);
          if (e >= 0) mbar_wait(ev_bar(bars, e), ev_par(e));
          if (pw == 0) mbar_expect_tx(fb, t < 0 ? 8 * UNIT : 6 * UNIT);
#pragma unroll
          for (int j = 0; j < 16 / RB; j++) {
#pragma unroll
            for (int i = 0; i < RB; i++) r[(j + 1) & 1][i] = lds32(ia + (RB * j + RB + i + (RB * j + RB >= 16) * 48) * NF * 4);
#pragma unroll
            for (int i = 0; i < RB; i++) tma_row_mc(d + (RB * j + i) * 128, &tmT, r[j & 1][i], fb);
          }
          if (t < 0) {
#pragma unroll
            for (int j = 0; j < 16 / RB; j++) {
              if (j + 1 < 16 / RB) {
#pragma unroll
                for (int i = 0; i < RB; i++) r[(j + 1) & 1][i] = lds32(ia + (64 + RB * j + RB + i) * NF * 4);
              }
#pragma unroll
              for (int i = 0; i < RB; i++) tma_row_mc(d + U_XB * UNIT + (RB * j + i) * 128, &tmT, r[j & 1][i], fb);
            }
          }
          tma_load(sb + (U_W + 4 * st + pw) * UNIT, &tmW, pw < 3 ? nt * 192 + pw * 64 : 1536 + (nt >> 2) * 64, f * 64, fb);
          if (f == GI && pw < 2) {
            if (pw == 0) mbar_expect_tx(bars + 8 * BAR_GIDX, 128 * NF * 4);
            bulk_load(sb + OFF_GIDX + pw * 64 * NF * 4, idx + ((ct >> 3) * 256 + (((ct >> 1) ^ pw) & 1) * 128 + (ct & 1) * 64) * NF, 64 * NF * 4, bars + 8 * BAR_GIDX);
          }
          if (f == GI && pw == 2) asm volatile("prefetch.tensormap [%0];" ::"l"(&tmC) : "memory");
          if (f + WD < NF) w_prefetch(w1, f + WD, ct, pw);
          if (++s == 3) s = 0;
        }
        mbar_wait(bars + 8 * BAR_T, 0);
#pragma unroll 1
        for (int ti = 0; ti < 8; ti++) {
          const int t = fresh(ti), pw = fresh(warp) - 8, e = t < 4 ? 22 - !t : 19 + t;
          const uint32_t ia = sb + OFF_TIDX + t * 256 + pw * 64, fb = bars + 8 * (BAR_FULL + ((NF + t) & 7));
          const uint32_t d = sb + b_x(t) * UNIT + ((fresh(cta) & 1) * 64 + pw * 16) * 128;
          int4 r[2];
          r[0] = lds128(ia);
          r[1] = lds128(ia + 16);
          mbar_wait(ev_bar(bars, e), ev_par(e));
          if (pw == 0) mbar_expect_tx(fb, t < 3 ? 2 * UNIT : 5 * UNIT);
#pragma unroll
          for (int j = 0; j < 4; j++) {
            tma_row_mc(d + (4 * j + 0) * 128, &tmT, r[j & 1].x, fb);
            tma_row_mc(d + (4 * j + 1) * 128, &tmT, r[j & 1].y, fb);
            tma_row_mc(d + (4 * j + 2) * 128, &tmT, r[j & 1].z, fb);
            tma_row_mc(d + (4 * j + 3) * 128, &tmT, r[j & 1].w, fb);
            if (j < 2) r[j & 1] = lds128(ia + 32 + 16 * j);
          }
        }
        mbar_arrive(bars + 8 * BAR_GDONE);
      }
      __syncwarp();
    }
    bar_sync<6, 128>();
    asm volatile("setmaxnreg.inc.sync.aligned.u32 %0;" ::"n"(PREG));
    {
    int cta; asm volatile("mov.u32 %0, %%ctaid.x;" : "=r"(cta));
    int tid; asm volatile("mov.u32 %0, %%tid.x;" : "=r"(tid));
    const int lane = tid & 31, pw = __shfl_sync(0xffffffffu, tid >> 5, 0) - 8;
    const bool gemm = cta < NGEMM;
    const int bt = cta >> 3, nt = cta & 7;
    const int ncin = cin_count(cta);
    unsigned epoch;
    auto load_cw = [&]() {
      if (elect1()) {
        asm volatile("fence.proxy.async.global;" ::: "memory");
        mbar_expect_tx(bars + 8 * BAR_CW, CW_BYTES);
        bulk_load(sb + OFF_CW, gp.s->cw, CW_CUT * 1792, bars + 8 * BAR_CW);
        bulk_load(sb + OFF_CW2, gp.s->cw + CW_CUT * 1792 / 16, (22 - CW_CUT) * 1792, bars + 8 * BAR_CW);
        bulk_load(sb + OFF_CWL, gp.s->cw + CW_MAIN / 16, CW_LIN, bars + 8 * BAR_CW);
      }
    };
    if (!gemm) {
      epoch = gp.s->epoch[cta] + 1;
#pragma unroll 1
      for (int i = pw * 32 + lane; i < NC_EXTRA * 13; i += 128)
        asm volatile("cp.async.ca.shared.global [%0], [%1], 8;" ::"r"(sb + XOFF_CIDX + i * 8), "l"(idx + cin_row(cta, i / 13) * NF + i % 13 * 2) : "memory");
      if (elect1()) {
#pragma unroll 1
        for (int i = 0; i < NPAIR; i++) mbar_init(sb + XOFF_BAR + (pw * NPAIR + i) * 8, pw & 1 ? 4 : 1);
        asm volatile("fence.mbarrier_init.release.cluster;" ::: "memory");
      }
      asm volatile("cp.async.wait_all;" ::: "memory");
      bar_sync<6, 128>();
      if (elect1()) mbar_arrive(bars + 8 * BAR_GDONE);
      __syncwarp();
      if (pw == 3) {
        flag_wait(&gp.s->foldflag, epoch * NEXTRA * 8, 0);
        __syncwarp();
        load_cw();
      }
      if (elect1()) {
        const int wg = pw & 1;
#pragma unroll 1
        for (int t = pw < 2 ? -1 : 1; t < NPAIR; t += t < 0 ? 1 : 2) {
          const int j = t < 0 ? 0 : 2 * t + 1, n = t < 0 || t == NPAIR - 1 ? 1 : 2;
          const uint32_t cb = t < 0 ? bars + 8 * (BAR_C0 + wg) : sb + XOFF_BAR + (wg * 2 * NPAIR + t) * 8;
          if (t == 0 || t == 1) mbar_wait(ev_bar(bars, EV_END), ev_par(EV_END));
          if (t >= 4) mbar_wait(cb + 8 * (NPAIR - 4), 0);
          mbar_expect_tx(cb, n * NF * 128);
#pragma unroll 1
          for (int i = 0; i < n; i++) {
            const uint32_t d = sb + (t < 0 ? OFF_GIDX + wg * XSLOT : XOFF_SLOT + (wg * 8 + (t & 3) * 2 + i) * XSLOT);
            const uint32_t ia = sb + XOFF_CIDX + (wg * (NC_EXTRA / 2) + j + i) * NF * 4;
#pragma unroll 1
            for (int k = 0; k < NF; k += 2) {
              const int2 r = lds64(ia + k * 4);
              tma_row(d + k * 128, &tmT, r.x, cb);
              tma_row(d + (k + 1) * 128, &tmT, r.y, cb);
            }
          }
        }
      }
      __syncwarp();
    } else {
      epoch = lds32(bars + 8 * BAR_EPOCH);
      if (pw == 3) {
        mbar_wait(ev_bar(bars, EV_CW), ev_par(EV_CW));
        load_cw();
      }
      constexpr int n0 = NC_WG0;
      const uint32_t ep = sb + OFF_EPI + (lane & 3) * 16, pk = sb + (pw * 32 + lane) * 16;
      float r2 = 0.f, r3 = 0.f;
      mbar_wait(bars + 8 * BAR_GDONE, 0);
      mbar_wait(bars + 8 * BAR_X0, 0);
      asm volatile("fence.proxy.async.global;" ::: "memory");
#pragma unroll 1
      for (int k = 0; k < 5; k++) {
        const int n = pw + 4 * k, wg = n > 1 && ((n & 1) || n == 2), j = n == 1 ? 1 : n < 3 ? 0 : n - 1 - wg;
        const int m = min((wg ? ncin - n0 : n0) - j, j ? 2 : 1), r = wg * n0 + j;
        const uint32_t cb = bars + 8 * (j ? BAR_CFULL + wg * 8 + (j >> 1) : BAR_C0 + wg), d = sb + slot_of(wg, j);
        if (n >= 2 && n < 12) {
          const int e = n == 2 ? EV_CW : n < 7 ? EV_SLOT : EV_END;
          mbar_wait(ev_bar(bars, e), ev_par(e));
        }
        auto load_sample = [&](int i) {
          const int4 u = lds128(sb + OFF_CIDX + (r + i) * 32), v = lds128(sb + OFF_CIDX + (r + i) * 32 + 16);
          const uint32_t a = d + i * XSLOT;
          tma_row(a, &tmC, (cta * 32 + r + i) * FS, cb);
          tma_row(a + (FS + 0) * 128, &tmT, u.x, cb);
          tma_row(a + (FS + 1) * 128, &tmT, u.y, cb);
          tma_row(a + (FS + 2) * 128, &tmT, u.z, cb);
          tma_row(a + (FS + 3) * 128, &tmT, u.w, cb);
          tma_row(a + (FS + 4) * 128, &tmT, v.x, cb);
          tma_row(a + (FS + 5) * 128, &tmT, v.y, cb);
          tma_row(a + (FS + 6) * 128, &tmT, v.z, cb);
          tma_row(a + (FS + 7) * 128, &tmT, v.w, cb);
        };
        if (m > 0 && elect1()) {
          mbar_expect_tx(cb, m * NF * 128);
#pragma unroll 1
          for (int i = 0; i < m; i++) load_sample(i);
        }
        __syncwarp();
        if (k == 0 || k == 4) continue;
        if (k == 1) {
          mbar_wait(bars + 8 * BAR_PARK, 0);
        }
        uint32_t a = k == 3 ? OFF_PARK2 : OFF_PARK + (k - 1) * 8 * 2048, b = (k - 1) * 8 * 64;
#pragma unroll 1
        for (const uint32_t e = b + 8 * 64; b != e; a += BGN * 2048, b += BGN * 64) {
          float4 v[BGN], q[BGN];
#pragma unroll
          for (int i = 0; i < BGN; i++) { v[i] = lds128f(pk, a + i * 2048); q[i] = lds128f(ep, b + i * 64); }
#pragma unroll
          for (int i = 0; i < BGN; i++) {
            r2 = gelu_acc(v[i].x, q[i].x, q[i].z, r2);
            r3 = gelu_acc(v[i].z, q[i].x, q[i].z, r3);
            r2 = gelu_acc(v[i].y, q[i].y, q[i].w, r2);
            r3 = gelu_acc(v[i].w, q[i].y, q[i].w, r3);
          }
        }
      }
      const float4 w = lds128f(pk + OFF_RS0);
      const int2 v = lds64(sb + OFF_RS1 + (pw * 32 + lane) * 8);
      uint2* dst = gp.s->part + (nt * NB + bt * 256 + pw * 16);
      const uint32_t o = (lane & 1) * 8 + (lane & 2) * 32 + (lane >> 2);
      put_tagged(dst + (o ^ ((cta & 2) * 64 + (~cta & 1) * 64)), quad_sum(w.x, w.y, w.z, w.w, lane), epoch);
      put_tagged(dst + (o ^ ((~cta & 2) * 64)), quad_sum(__int_as_float(v.x), __int_as_float(v.y), r2, r3, lane), epoch);
    }
    if (pw == 3 || !gemm) {
      float s = (sb & 0xFFFFFF) == SMEM_BASE ? bf2f(bout[0]) : __int_as_float(0x7fc00000);
      const int r = gemm ? lane : pw * (NC_EXTRA / 4) + min(lane, NC_EXTRA / 4 - 1), row = cin_row(cta, r);
      const uint2* src = gp.s->part + row;
      uint2 v[8];
#pragma unroll 1
      for (int i = 0; i < 100000; i++) {
        unsigned miss = 0;
#pragma unroll
        for (int n = 0; n < 8; n++)
          asm volatile("ld.relaxed.gpu.global.v2.b32 {%0, %1}, [%2];" : "=r"(v[n].x), "=r"(v[n].y) : "l"(src + n * NB) : "memory");
#pragma unroll
        for (int n = 0; n < 8; n++) miss |= v[n].y ^ epoch;
        if (__all_sync(0xffffffffu, miss == 0)) break;
        __nanosleep(POLL);
      }
#pragma unroll
      for (int n = 0; n < 8; n++) s += __uint_as_float(v[n].x);
      sts64f(sb + OFF_DNN + r * 8, s, __int_as_float(row));
      __syncwarp();
      if (lane == 0) mbar_arrive(bars + 8 * BAR_DNN);
      if (pw == 3 && lane == 0) gp.s->epoch[fresh(cta)] = epoch;
    }
    }
  } else {
    const int wg = warp >> 2;
    const int p = tid & 127;
    if (gemm) {
      asm volatile("barrier.cluster.arrive.relaxed.aligned;" ::: "memory");
#pragma unroll
      for (int i = 0; i < 4; i++) {
        const int r = __shfl_sync(0xffffffffu, myidx, 8 * i + 2 * (lane >> 3));
        const int row = warp * 16 + 4 * i + (lane >> 3);
        cpasync16(sb + row * 128 + (((lane & 7) ^ (row & 7)) << 4), table + (size_t)r * 64 + (lane & 7) * 8);
      }
      asm volatile("barrier.cluster.wait.acquire.aligned;" ::: "memory");
    } else {
      fold_weights(smem, sb, cta - NGEMM, wco, gp);
    }
    asm volatile("setmaxnreg.inc.sync.aligned.u32 224;");
    float r0 = 0.f, r1 = 0.f, r2 = 0.f, r3 = 0.f;
    CinCtx c;
    float accA[28];
    uint32_t xA[10][2], z[8];
    const uint32_t ep = sb + OFF_EPI + (lane & 3) * 16;
    auto load_w = [&](int t) {
      const int w = warp & 3;
      if (w < 3 && elect1())
        tma_load(sb + (b_w(t) + b_ws(t) * w) * UNIT, &tmW, nt * 192 + w * 64, (NF - 1 - t) * 64, bars + 8 * (BAR_FULL + ((NF + t) & 7)));
    };
    auto keep_x = [&](int f, int u) {
      if (warp == 0 && elect1()) tma_store(&tmS, f * 64, cta * 32, sb + (u + rank) * UNIT + (nt >> 2) * 4096);
    };
    auto role = [&](int w) { int c; asm volatile("mov.u32 %0, %%ctaid.x;" : "=r"(c)); return c < NGEMM && wg == w; };
    if (role(0)) {
      bar_sync<1, 128>();
      asm volatile("setmaxnreg.inc.sync.aligned.u32 256;");
      float d0[96], dx[32], dw[96];
      Gelu<24> g0;
      mbar_wait(bars + 8 * BAR_W0, 0);
      asm volatile("cp.async.wait_all;" ::: "memory");
      asm volatile("fence.proxy.async.shared::cta;" ::: "memory");
      bar_sync<2, 256>();
      const uint64_t dA0 = desc_x(rank), dA1 = desc_x(rank ^ 1);
      wg_fence();
#pragma unroll
      for (int k = 0; k < 4; k++) {
        wgmma_ss_n256(dw, dx, dA0 + 2 * k, desc_w(U_W) + 128 * k, k != 0);
        wgmma_ss_n192(d0, dA1 + 2 * k, desc_w(U_W) + 128 * k, k != 0);
      }
      wg_commit();
      keep_x(0, 0);
#pragma unroll 1
      for (int f = 1; f < NF - 3; f++) {
        mbar_wait(bars + 8 * (BAR_FULL + (f & 7)), (f >> 3) & 1);
        const int st = (STAGES >> (2 * f)) & 3, xo = (st == 3 ? U_SP : 2 * st) * (UNIT / 16);
        const uint64_t dB = desc_w(U_W + 4 * st);
        wg_fence();
        wgmma_ss_n256(dw, dx, dA0 + xo, dB, 1);
        wgmma_ss_n192(d0, dA1 + xo, dB, 1);
        wg_commit();
        store_read<0>();
        wg_wait<1>();
        if (p < (f > FS ? 4 : 2)) mbar_arrive_cta(ev_bar(bars, f - 1), p & 1);
#pragma unroll
        for (int k = 1; k < 4; k++) {
          wgmma_ss_n256(dw, dx, dA0 + xo + 2 * k, dB + 128 * k, 1);
          wgmma_ss_n192(d0, dA1 + xo + 2 * k, dB + 128 * k, 1);
        }
        wg_commit();
        if (f < FS) keep_x(f, 2 * st);
      }
      {
        constexpr int x3 = 2 * (UNIT / 16), x4 = U_SP * (UNIT / 16), x5 = 4 * (UNIT / 16);
        const uint64_t dB3 = desc_w(U_W + 4), dB4 = desc_w(U_W + 12), dB5 = desc_w(U_W + 8);
        mbar_wait(bars + 8 * (BAR_FULL + 7), 0);
        tile_step(d0, dA1 + x3, dB3);
        wg_wait<1>();
        if (p < 4) mbar_arrive_cta(ev_bar(bars, NF - 4), p & 1);
        mbar_wait(bars + 8 * (BAR_FULL + 0), 1);
        tile_step(d0, dA1 + x4, dB4);
        mbar_wait(bars + 8 * (BAR_FULL + 1), 1);
        tile_step(d0, dA1 + x5, dB5);
        wide_step(dw, dx, dA0 + x3, dB3);
        g0.start(ep);
        wg_wait<1>();
        wide_step(dw, dx, dA0 + x4, dB4);
        g0.part<0, PE1>(d0, r0, r1, bars + 8 * BAR_W0);
        pin(r0, r1, ep, gp.zero);
        wg_wait<1>();
        if (p < 4) mbar_arrive_cta(ev_bar(bars, NF - 3), p & 1);
        wide_step<0, HK>(dw, dx, dA0 + x5, dB5);
        g0.part<PE1, PE2>(d0, r0, r1, bars + 8 * BAR_W0);
        pin(r0, r1, ep, gp.zero);
        wg_wait<1>();
        bar_arrive<4, 256>();
        if (p < 4) mbar_arrive_cta(ev_bar(bars, NF - 2), p & 1);
        wide_step<HK, 4>(dw, dx, dA0 + x5, dB5);
        g0.part<PE2, PE0>(d0, r0, r1);
        pin(r0, r1, ep, gp.zero);
        wg_wait<0>();
        load_w(3);
        if (p < 4) mbar_arrive_cta(ev_bar(bars, NF - 1), p & 1);
        asm volatile("cp.async.bulk.wait_group 0;" ::: "memory");
        if (warp == 0 && elect1()) mbar_arrive(bars + 8 * BAR_X0);
      }
      g0.part<PE0, 24>(d0, r0, r1);
      Gelu<8> gx;
      gx.start(ep + 24 * 64);
      gx.part<0, 8>(dx, r2, r3);
      float d1[96];
      hand_on(d1, dw);
      asm volatile("setmaxnreg.dec.sync.aligned.u32 224;");
      Gelu<24> g1;
      g1.start(ep);
      g1.part<0, 24>(d1, r2, r3);
    }
    if (role(1)) {
      float d0[96], dw[96];
      asm volatile("cp.async.wait_all;" ::: "memory");
      asm volatile("fence.proxy.async.shared::cta;" ::: "memory");
      bar_arrive<2, 256>();
      {
        const int col = p < 96 ? nt * 96 + p : 768 + (nt >> 2) * 32 + (p - 96);
        const uint32_t bb = __ldg(reinterpret_cast<const uint32_t*>(b1) + col), ww = __ldg(reinterpret_cast<const uint32_t*>(w2) + col);
        reinterpret_cast<float4*>(smem + OFF_EPI)[p] =
            make_float4(ALPHA * bf_lo(bb), ALPHA * bf_hi(bb), (0.5f / ALPHA) * bf_lo(ww), (0.5f / ALPHA) * bf_hi(ww));
      }
      mbar_wait(bars + 8 * BAR_W0, 0);
      mbar_wait(bars + 8 * BAR_FULL, 0);
      wg_fence();
#pragma unroll
      for (int k = 0; k < 4; k++) {
        wgmma_ss_n192(d0, desc_x(U_XB) + 2 * k, desc_w(U_W) + 128 * k, k != 0);
        wgmma_ss_n192(dw, desc_x(U_XB + 1) + 2 * k, desc_w(U_W) + 128 * k, k != 0);
      }
      wg_commit();
      int s = 1;
#pragma unroll 1
      for (int f = 1; f < FS; f++) {
        mbar_wait(bars + 8 * (BAR_FULL + (f & 7)), (f >> 3) & 1);
        const uint64_t dA = desc_x(U_XB + 2 * s), dB = desc_w(U_W + 4 * s);
        wg_fence();
        wgmma_ss_n192(d0, dA, dB, 1);
        wgmma_ss_n192(dw, dA + 512, dB, 1);
        wg_commit();
        wg_wait<1>();
        if (p < 2) mbar_arrive_cta(ev_bar(bars, f - 1), p);
#pragma unroll
        for (int k = 1; k < 4; k++) {
          wgmma_ss_n192(d0, dA + 2 * k, dB + 128 * k, 1);
          wgmma_ss_n192(dw, dA + 512 + 2 * k, dB + 128 * k, 1);
        }
        wg_commit();
        if (++s == 3) s = 0;
      }
      wg_wait<0>();
      if (p < 2) mbar_arrive_cta(ev_bar(bars, FS - 1), p);
      {
        const uint32_t a = sb + OFF_GIDX + 64 * NF * 4;
        int v[4];
#pragma unroll
        for (int i = 0; i < 4; i++) v[i] = lds32(a + (((p & 15) * 4 + i) * NF + (NF - 1 - (p >> 4))) * 4);
        const int2 w = lds64(sb + OFF_GIDX + (((nt >> 2) * 32 + (p >> 2)) * NF + FS + (p & 3) * 2) * 4);
        asm volatile("st.shared.v2.b32 [%0], {%1, %2};" ::"r"(sb + OFF_CIDX + p * 8), "r"(w.x), "r"(w.y) : "memory");
        bar_sync<3, 128>();
        asm volatile("st.shared.v4.b32 [%0], {%1, %2, %3, %4};" ::"r"(sb + OFF_TIDX + p * 16), "r"(v[0]), "r"(v[1]), "r"(v[2]), "r"(v[3]) : "memory");
        bar_sync<3, 128>();
        if (p < 2) {
          const unsigned epoch = gp.s->epoch[cta] + 1;
          flag_wait(&gp.s->foldflag, epoch * NEXTRA * 8, 0);
          sts32f(bars + 8 * BAR_EPOCH, __uint_as_float(epoch));
          mbar_arrive(bars + 8 * BAR_T);
        }
        __syncwarp();
      }
      mbar_wait(ev_bar(bars, FS), ev_par(FS));
      mbar_wait(bars + 8 * (BAR_FULL + 2), 1);
      bar_sync<4, 256>();
#pragma unroll
      for (int t = 0; t < 4; t++) {
        if (t) mbar_wait(bars + 8 * (BAR_FULL + 2 + t), 1);
        const uint64_t dA = desc_x(b_x(t)), dB = desc_w(b_w(t), b_ws(t));
        wg_fence();
#pragma unroll
        for (int k = 0; k < 4; k++) {
          wgmma_ss_n192(d0, dA + 2 * k, dB + 128 * k, 1);
          wgmma_ss_n192(dw, dA + 512 + 2 * k, dB + 128 * k, 1);
          if (k == 1 && t) {
            wg_commit();
            wg_wait<1>();
            wg_fence();
          }
        }
        wg_commit();
        if (t) {
          if (t == 1) mbar_wait(ev_bar(bars, NF - 1), ev_par(NF - 1));
          load_w(3 + t);
          if (t == 1 && p < 4) mbar_arrive_cta(ev_bar(bars, 26), p & 1);
        }
      }
      mbar_wait(bars + 8 * (BAR_FULL + 6), 1);
      tile_step(d0, desc_x(b_x(4)), desc_w(b_w(4)));
      wg_wait<1>();
      load_w(7);
      if (p < 4) mbar_arrive(ev_bar(bars, EV_CW));
      mbar_wait(bars + 8 * (BAR_FULL + 7), 1);
      tile_step(d0, desc_x(b_x(5)), desc_w(b_w(5)));
      mbar_wait(bars + 8 * (BAR_FULL + 0), 0);
      tile_step(d0, desc_x(b_x(6)), desc_w(b_w(6)));
      mbar_wait(bars + 8 * (BAR_FULL + 1), 0);
      tile_step(d0, desc_x(b_x(7)), desc_w(b_w(7), 4));
      tile_step(dw, desc_x(b_x(4) + 1), desc_w(b_w(4)));
      Gelu<24> g0;
      g0.start(ep);
      wg_wait<1>();
      tile_step(dw, desc_x(b_x(5) + 1), desc_w(b_w(5)));
      g0.part<0, PS>(d0, r0, r1);
      pin(r0, r1, ep, gp.zero);
      wg_wait<1>();
      if (p < 4) mbar_arrive(ev_bar(bars, 30));
      tile_step(dw, desc_x(b_x(6) + 1), desc_w(b_w(6)));
      g0.part<PS, PS + PS2>(d0, r0, r1);
      pin(r0, r1, ep, gp.zero);
      wg_wait<1>();
      tile_step(dw, desc_x(b_x(7) + 1), desc_w(b_w(7), 4));
      g0.part<PS + PS2, 24>(d0, r0, r1);
      sts64f(sb + OFF_RS1 + p * 8, r0, r1);
      cin_begin(c, sb, 1, slot_of(1, 0), xA, accA, z);
      if (p < 4) mbar_arrive(ev_bar(bars, EV_END));
#pragma unroll
      for (int i = 0; i < 24; i++)
        sts128f(sb + p * 16 + (i < 16 ? OFF_PARK + i * 2048 : OFF_PARK2 + (i - 16) * 2048), dw[4 * i], dw[4 * i + 1], dw[4 * i + 2], dw[4 * i + 3]);
      __syncwarp();
      if (lane == 0) mbar_arrive(bars + 8 * BAR_PARK);
    }
    if (!role(1)) {
      cin_begin(c, sb, wg, OFF_GIDX + wg * XSLOT, xA, accA, z);
      sts128f(sb + OFF_RS0 + p * 16, r0, r1, r2, r3);
      __syncwarp();
      if (lane == 0) mbar_arrive(bars + 8 * BAR_PARK);
    }

    {
    int cta, tid;
    asm volatile("mov.u32 %0, %%ctaid.x;" : "=r"(cta));
    asm volatile("mov.u32 %0, %%tid.x;" : "=r"(tid));
    cta = __shfl_sync(0xffffffffu, cta, 0);
    const bool gemm = cta < NGEMM;
    const int p = tid & 127, wg = __shfl_sync(0xffffffffu, tid >> 7, 0);
    const int ncin = cin_count(cta);
    const int n0 = gemm ? NC_WG0 : NC_EXTRA / 2;
    const int rb = wg ? n0 : 0;
    const int nj = wg ? ncin - n0 : n0;
    cin_setup(c, sb, wg, p, gemm, nj, gp.zero);
    uint32_t fa = sb + (gemm ? slot_of(wg, (p >> 3) + 1) + NF * 128 : (wg ? XOFF_CIN1 : XOFF_CIN0) + (p >> 3) * CROW) + (p & 7) * 16, fd = sb + OFF_DNN + rb * 8;
    asm volatile("" : "+r"(fa), "+r"(fd));
    auto wg_sync = [&]() { if (wg == 0) bar_sync<1, 128>(); else bar_sync<3, 128>(); };
    mbar_wait(gemm ? bars + 8 * BAR_GDONE : ev_bar(bars, EV_END), 0);
    cin_run(c, nj, xA, accA, z, [&]() {
      mbar_wait(bars + 8 * BAR_DNN, 0);
    }, [&](int j) {
    });
    int2 dn = lds64(fd + (p >> 3) * 8);
    __nv_bfloat16* op = out + dn.y;
    float d = (p & 7) == 0 ? __int_as_float(dn.x) : 0.f;
    asm volatile("" : "+f"(d), "+l"(op));
    wg_sync();
#pragma unroll 1
    for (int r = 0;;) {
      const float4 v0 = lds128f(fa), v1 = lds128f(fa + 128), v2 = lds128f(fa + 256), v3 = lds128f(fa + 384);
      float s = (((v0.x + v0.y) + (v0.z + v0.w)) + ((v1.x + v1.y) + (v1.z + v1.w))) +
                (((v2.x + v2.y) + (v2.z + v2.w)) + (((v3.x + v3.y) + d) + (v3.z + v3.w)));
      s += __shfl_xor_sync(0xffffffffu, s, 1);
      s += __shfl_xor_sync(0xffffffffu, s, 2);
      s += __shfl_xor_sync(0xffffffffu, s, 4);
      if ((p & 7) == 0 && r + (p >> 3) < nj) *op = __float2bfloat16(s);
      r += 16;
      if (r >= nj) break;
      fa += 16 * CROW;
      dn = lds64(fd + (r + (p >> 3)) * 8);
      op = out + dn.y;
      d = (p & 7) == 0 ? __int_as_float(dn.x) : 0.f;
    }
    }
  }
}

typedef CUresult (*EncodeFn)(CUtensorMap*, CUtensorMapDataType, cuuint32_t, void*, const cuuint64_t*, const cuuint64_t*,
                             const cuuint32_t*, const cuuint32_t*, CUtensorMapInterleave, CUtensorMapSwizzle,
                             CUtensorMapL2promotion, CUtensorMapFloatOOBfill);

extern "C" void kernel_launch(void* const* d_in, const int* in_sizes, int n_in, void* d_out, int out_size) {
  void* fn = nullptr;
  cudaDriverEntryPointQueryResult q;
  cudaGetDriverEntryPoint("cuTensorMapEncodeTiled", &fn, cudaEnableDefault, &q);
  EncodeFn enc = (EncodeFn)fn;
  CUtensorMap tmW, tmT, tmS, tmC;
  const cuuint32_t es[3] = {1, 1, 1};
  {
    cuuint64_t dims[2] = {DIN, DIN}, st[1] = {DIN * 2};
    cuuint32_t box[2] = {64, 64};
    enc(&tmW, CU_TENSOR_MAP_DATA_TYPE_BFLOAT16, 2, d_in[4], dims, st, box, es, CU_TENSOR_MAP_INTERLEAVE_NONE,
        CU_TENSOR_MAP_SWIZZLE_128B, CU_TENSOR_MAP_L2_PROMOTION_NONE, CU_TENSOR_MAP_FLOAT_OOB_FILL_NONE);
  }
  {
    cuuint64_t dims[2] = {64, (cuuint64_t)(in_sizes[1] / 64)}, st[1] = {128};
    cuuint32_t box[2] = {64, 1};
    enc(&tmT, CU_TENSOR_MAP_DATA_TYPE_BFLOAT16, 2, d_in[1], dims, st, box, es, CU_TENSOR_MAP_INTERLEAVE_NONE,
        CU_TENSOR_MAP_SWIZZLE_128B, CU_TENSOR_MAP_L2_PROMOTION_NONE, CU_TENSOR_MAP_FLOAT_OOB_FILL_NONE);
  }
  void* x0 = nullptr;
  cudaGetSymbolAddress(&x0, g_x0);
  {
    cuuint64_t dims[2] = {FS * 64, NB}, st[1] = {FS * 128};
    cuuint32_t box[2] = {64, NC_GEMM + 1};
    enc(&tmS, CU_TENSOR_MAP_DATA_TYPE_BFLOAT16, 2, x0, dims, st, box, es, CU_TENSOR_MAP_INTERLEAVE_NONE,
        CU_TENSOR_MAP_SWIZZLE_128B, CU_TENSOR_MAP_L2_PROMOTION_NONE, CU_TENSOR_MAP_FLOAT_OOB_FILL_NONE);
  }
  {
    cuuint64_t dims[2] = {64, NB * FS}, st[1] = {128};
    cuuint32_t box[2] = {64, FS};
    enc(&tmC, CU_TENSOR_MAP_DATA_TYPE_BFLOAT16, 2, x0, dims, st, box, es, CU_TENSOR_MAP_INTERLEAVE_NONE,
        CU_TENSOR_MAP_SWIZZLE_128B, CU_TENSOR_MAP_L2_PROMOTION_NONE, CU_TENSOR_MAP_FLOAT_OOB_FILL_NONE);
  }
  GPtr gp;
  gp.zero = 0;
  cudaGetSymbolAddress((void**)&gp.s, g_scratch);
  cudaGetSymbolAddress((void**)&gp.tab, g_slot_tab);
  cudaFuncSetAttribute(xdeepfm_kernel, cudaFuncAttributeMaxDynamicSharedMemorySize, SMEM_BYTES);
  xdeepfm_kernel<<<GRID, 384, SMEM_BYTES, cudaStreamPerThread>>>(
      (const int*)d_in[0], (const __nv_bfloat16*)d_in[1], (const __nv_bfloat16*)d_in[4], (const __nv_bfloat16*)d_in[5],
      (const __nv_bfloat16*)d_in[6], (const __nv_bfloat16*)d_in[2], (const __nv_bfloat16*)d_in[3],
      (const __nv_bfloat16*)d_in[7], (__nv_bfloat16*)d_out, gp, tmW, tmT, tmS, tmC);
}
```

```cpp
#include <cuda_runtime.h>
#include <cuda_bf16.h>
#include <cuda.h>
#include <stdint.h>

__device__ __forceinline__ void wgmma_ss_n256(float (&d)[96], float (&e)[32], uint64_t descA, uint64_t descB, int scaleD) {
  asm volatile("{\n.reg .pred p;\nsetp.ne.b32 p, %130, 0;\n"
      "wgmma.mma_async.sync.aligned.m64n256k16.f32.bf16.bf16 {"
      "%0, %1, %2, %3, %4, %5, %6, %7, %8, %9, %10, %11, %12, %13, %14, %15,"
      "%16, %17, %18, %19, %20, %21, %22, %23, %24, %25, %26, %27, %28, %29, %30, %31,"
      "%32, %33, %34, %35, %36, %37, %38, %39, %40, %41, %42, %43, %44, %45, %46, %47,"
      "%48, %49, %50, %51, %52, %53, %54, %55, %56, %57, %58, %59, %60, %61, %62, %63,"
      "%64, %65, %66, %67, %68, %69, %70, %71, %72, %73, %74, %75, %76, %77, %78, %79,"
      "%80, %81, %82, %83, %84, %85, %86, %87, %88, %89, %90, %91, %92, %93, %94, %95,"
      "%96, %97, %98, %99, %100, %101, %102, %103, %104, %105, %106, %107, %108, %109, %110, %111,"
      "%112, %113, %114, %115, %116, %117, %118, %119, %120, %121, %122, %123, %124, %125, %126, %127"
      "}, %128, %129, p, 1, 1, 0, 1;\n}\n"
      : "+f"(d[0]), "+f"(d[1]), "+f"(d[2]), "+f"(d[3]), "+f"(d[4]), "+f"(d[5]), "+f"(d[6]), "+f"(d[7]),
        "+f"(d[8]), "+f"(d[9]), "+f"(d[10]), "+f"(d[11]), "+f"(d[12]), "+f"(d[13]), "+f"(d[14]), "+f"(d[15]),
        "+f"(d[16]), "+f"(d[17]), "+f"(d[18]), "+f"(d[19]), "+f"(d[20]), "+f"(d[21]), "+f"(d[22]), "+f"(d[23]),
        "+f"(d[24]), "+f"(d[25]), "+f"(d[26]), "+f"(d[27]), "+f"(d[28]), "+f"(d[29]), "+f"(d[30]), "+f"(d[31]),
        "+f"(d[32]), "+f"(d[33]), "+f"(d[34]), "+f"(d[35]), "+f"(d[36]), "+f"(d[37]), "+f"(d[38]), "+f"(d[39]),
        "+f"(d[40]), "+f"(d[41]), "+f"(d[42]), "+f"(d[43]), "+f"(d[44]), "+f"(d[45]), "+f"(d[46]), "+f"(d[47]),
        "+f"(d[48]), "+f"(d[49]), "+f"(d[50]), "+f"(d[51]), "+f"(d[52]), "+f"(d[53]), "+f"(d[54]), "+f"(d[55]),
        "+f"(d[56]), "+f"(d[57]), "+f"(d[58]), "+f"(d[59]), "+f"(d[60]), "+f"(d[61]), "+f"(d[62]), "+f"(d[63]),
        "+f"(d[64]), "+f"(d[65]), "+f"(d[66]), "+f"(d[67]), "+f"(d[68]), "+f"(d[69]), "+f"(d[70]), "+f"(d[71]),
        "+f"(d[72]), "+f"(d[73]), "+f"(d[74]), "+f"(d[75]), "+f"(d[76]), "+f"(d[77]), "+f"(d[78]), "+f"(d[79]),
        "+f"(d[80]), "+f"(d[81]), "+f"(d[82]), "+f"(d[83]), "+f"(d[84]), "+f"(d[85]), "+f"(d[86]), "+f"(d[87]),
        "+f"(d[88]), "+f"(d[89]), "+f"(d[90]), "+f"(d[91]), "+f"(d[92]), "+f"(d[93]), "+f"(d[94]), "+f"(d[95]),
        "+f"(e[0]), "+f"(e[1]), "+f"(e[2]), "+f"(e[3]), "+f"(e[4]), "+f"(e[5]), "+f"(e[6]), "+f"(e[7]),
        "+f"(e[8]), "+f"(e[9]), "+f"(e[10]), "+f"(e[11]), "+f"(e[12]), "+f"(e[13]), "+f"(e[14]), "+f"(e[15]),
        "+f"(e[16]), "+f"(e[17]), "+f"(e[18]), "+f"(e[19]), "+f"(e[20]), "+f"(e[21]), "+f"(e[22]), "+f"(e[23]),
        "+f"(e[24]), "+f"(e[25]), "+f"(e[26]), "+f"(e[27]), "+f"(e[28]), "+f"(e[29]), "+f"(e[30]), "+f"(e[31])
      : "l"(descA), "l"(descB), "r"(scaleD));
}
__device__ __forceinline__ void wgmma_ss_n192(float (&d)[96], uint64_t descA, uint64_t descB, int scaleD) {
  asm volatile("{\n.reg .pred p;\nsetp.ne.b32 p, %98, 0;\n"
      "wgmma.mma_async.sync.aligned.m64n192k16.f32.bf16.bf16 {"
      "%0, %1, %2, %3, %4, %5, %6, %7, %8, %9, %10, %11, %12, %13, %14, %15,"
      "%16, %17, %18, %19, %20, %21, %22, %23, %24, %25, %26, %27, %28, %29, %30, %31,"
      "%32, %33, %34, %35, %36, %37, %38, %39, %40, %41, %42, %43, %44, %45, %46, %47,"
      "%48, %49, %50, %51, %52, %53, %54, %55, %56, %57, %58, %59, %60, %61, %62, %63,"
      "%64, %65, %66, %67, %68, %69, %70, %71, %72, %73, %74, %75, %76, %77, %78, %79,"
      "%80, %81, %82, %83, %84, %85, %86, %87, %88, %89, %90, %91, %92, %93, %94, %95"
      "}, %96, %97, p, 1, 1, 0, 1;\n}\n"
      : "+f"(d[0]), "+f"(d[1]), "+f"(d[2]), "+f"(d[3]), "+f"(d[4]), "+f"(d[5]), "+f"(d[6]), "+f"(d[7]),
        "+f"(d[8]), "+f"(d[9]), "+f"(d[10]), "+f"(d[11]), "+f"(d[12]), "+f"(d[13]), "+f"(d[14]), "+f"(d[15]),
        "+f"(d[16]), "+f"(d[17]), "+f"(d[18]), "+f"(d[19]), "+f"(d[20]), "+f"(d[21]), "+f"(d[22]), "+f"(d[23]),
        "+f"(d[24]), "+f"(d[25]), "+f"(d[26]), "+f"(d[27]), "+f"(d[28]), "+f"(d[29]), "+f"(d[30]), "+f"(d[31]),
        "+f"(d[32]), "+f"(d[33]), "+f"(d[34]), "+f"(d[35]), "+f"(d[36]), "+f"(d[37]), "+f"(d[38]), "+f"(d[39]),
        "+f"(d[40]), "+f"(d[41]), "+f"(d[42]), "+f"(d[43]), "+f"(d[44]), "+f"(d[45]), "+f"(d[46]), "+f"(d[47]),
        "+f"(d[48]), "+f"(d[49]), "+f"(d[50]), "+f"(d[51]), "+f"(d[52]), "+f"(d[53]), "+f"(d[54]), "+f"(d[55]),
        "+f"(d[56]), "+f"(d[57]), "+f"(d[58]), "+f"(d[59]), "+f"(d[60]), "+f"(d[61]), "+f"(d[62]), "+f"(d[63]),
        "+f"(d[64]), "+f"(d[65]), "+f"(d[66]), "+f"(d[67]), "+f"(d[68]), "+f"(d[69]), "+f"(d[70]), "+f"(d[71]),
        "+f"(d[72]), "+f"(d[73]), "+f"(d[74]), "+f"(d[75]), "+f"(d[76]), "+f"(d[77]), "+f"(d[78]), "+f"(d[79]),
        "+f"(d[80]), "+f"(d[81]), "+f"(d[82]), "+f"(d[83]), "+f"(d[84]), "+f"(d[85]), "+f"(d[86]), "+f"(d[87]),
        "+f"(d[88]), "+f"(d[89]), "+f"(d[90]), "+f"(d[91]), "+f"(d[92]), "+f"(d[93]), "+f"(d[94]), "+f"(d[95])
      : "l"(descA), "l"(descB), "r"(scaleD));
}
template <unsigned long long DESC, int SCALE>
__device__ __forceinline__ void wgmma_rs_n56(float (&d)[28], uint32_t a0, uint32_t a1, uint32_t a2, uint32_t a3) {
  asm volatile("{\n.reg .b64 desc;\nmov.b64 desc, %32;\n"
      "wgmma.mma_async.sync.aligned.m64n56k16.f32.bf16.bf16 {"
      "%0, %1, %2, %3, %4, %5, %6, %7, %8, %9, %10, %11, %12, %13, %14, %15,"
      "%16, %17, %18, %19, %20, %21, %22, %23, %24, %25, %26, %27"
      "}, {%28, %29, %30, %31}, desc, %33, 1, 1, 0;\n}\n"
      : "+f"(d[0]), "+f"(d[1]), "+f"(d[2]), "+f"(d[3]), "+f"(d[4]), "+f"(d[5]), "+f"(d[6]), "+f"(d[7]),
        "+f"(d[8]), "+f"(d[9]), "+f"(d[10]), "+f"(d[11]), "+f"(d[12]), "+f"(d[13]), "+f"(d[14]), "+f"(d[15]),
        "+f"(d[16]), "+f"(d[17]), "+f"(d[18]), "+f"(d[19]), "+f"(d[20]), "+f"(d[21]), "+f"(d[22]), "+f"(d[23]),
        "+f"(d[24]), "+f"(d[25]), "+f"(d[26]), "+f"(d[27])
      : "r"(a0), "r"(a1), "r"(a2), "r"(a3), "n"(DESC), "n"(SCALE));
}
template <unsigned long long DESC, int SCALE>
__device__ __forceinline__ void wgmma_rs_n32(float (&d)[28], uint32_t a0, uint32_t a1, uint32_t a2, uint32_t a3) {
  asm volatile("{\n.reg .b64 desc;\nmov.b64 desc, %20;\n"
      "wgmma.mma_async.sync.aligned.m64n32k16.f32.bf16.bf16 {"
      "%0, %1, %2, %3, %4, %5, %6, %7, %8, %9, %10, %11, %12, %13, %14, %15"
      "}, {%16, %17, %18, %19}, desc, %21, 1, 1, 0;\n}\n"
      : "+f"(d[0]), "+f"(d[1]), "+f"(d[2]), "+f"(d[3]), "+f"(d[4]), "+f"(d[5]), "+f"(d[6]), "+f"(d[7]),
        "+f"(d[8]), "+f"(d[9]), "+f"(d[10]), "+f"(d[11]), "+f"(d[12]), "+f"(d[13]), "+f"(d[14]), "+f"(d[15])
      : "r"(a0), "r"(a1), "r"(a2), "r"(a3), "n"(DESC), "n"(SCALE));
}

constexpr int NB = 4096, NF = 26, DIN = 1664;
constexpr int NGEMM = 128, NEXTRA = 4, GRID = NGEMM + NEXTRA;
constexpr int NC_EXTRA = 80;
constexpr int NC_WG0 = 16;
constexpr int HK = 4;
constexpr int PE0 = 9;
constexpr int WD = 2;
constexpr int GI = 3;
constexpr int PE1 = 4;
constexpr int PE2 = 8;
constexpr int PS2 = 6;
constexpr int POLL = 400;
constexpr int BGN = 1;
constexpr int XD = 1000;
constexpr int PREG = 40;
constexpr int PS = 6;
constexpr int RB = 4;
constexpr int NC_GEMM = 29, NBIG = NB - NGEMM * NC_GEMM - NEXTRA * NC_EXTRA;
static_assert(NBIG >= 0 && NBIG <= NGEMM && NC_EXTRA % 4 == 0 && NC_EXTRA <= 96, "split");
constexpr int CW_MAIN = 22 * 1792, CW_LIN = 2 * 1024, CW_BYTES = CW_MAIN + CW_LIN;
constexpr int XSLOT = 4096;

constexpr int UNIT = 8192, FS = 18;
constexpr int U_W = 6, U_XB = 18, U_SP = 24;
constexpr int CW_CUT = 9;
constexpr int OFF_CW = 0, OFF_CW2 = 6 * UNIT, OFF_CWL = 9 * UNIT;
constexpr int CROW = 528;
constexpr int OFF_PARK = 10 * UNIT, OFF_PARK2 = 24 * UNIT;
constexpr int OFF_RS0 = OFF_CWL + CW_LIN, OFF_RS1 = OFF_CWL - 1024;
constexpr int OFF_GIDX = 26 * UNIT;
constexpr int OFF_TIDX = OFF_GIDX + 128 * NF * 4 - 8 * 64 * 4;
constexpr int OFF_CIDX = OFF_GIDX + 128 * NF * 4;
constexpr int OFF_EPI = OFF_CIDX + 32 * 8 * 4;
constexpr int OFF_DNN = OFF_EPI + 128 * 16;
constexpr int OFF_BAR = OFF_DNN + 112 * 8;
constexpr int SMEM_BYTES = OFF_BAR + 92 * 8;
static_assert(CW_CUT * 1792 <= 2 * UNIT && (22 - CW_CUT) * 1792 <= 3 * UNIT , "smem");
constexpr uint32_t SMEM_BASE = 1024;
static_assert(SMEM_BYTES <= 232448, "smem");
static_assert(OFF_EPI % 16 == 0 && OFF_BAR % 8 == 0, "align");
constexpr int XOFF_W3 = 0, XOFF_W2 = 35152, XOFF_W1 = 70304, XOFF_M = XOFF_W1 + 8 * 1352, XOFF_S = XOFF_M + 32 * 40 * 4,
              XOFF_SLOT = 10 * UNIT, XOFF_CIN0 = 2 * UNIT, XOFF_CIN1 = 18 * UNIT, XOFF_CIDX = 22 * UNIT,
              XOFF_BAR = 24 * UNIT, NPAIR = NC_EXTRA / 4;
static_assert(XOFF_S + 14 * 3136 <= 21 * UNIT && 48 * CROW <= 4 * UNIT, "smem");

constexpr int BAR_PARK = 0,
              BAR_CW = 1,
              BAR_GIDX = 2,
              BAR_X0 = 3,
              BAR_W0 = 4,
              BAR_DNN = 5,
              BAR_T = 6,
              BAR_GDONE = 7,
              BAR_EPOCH = 8,
              BAR_C0 = 9,
              BAR_CFULL = 11,
              BAR_FULL = 27,
              BAR_EV = 61,
              BAR_END = 92;
constexpr int EV_CW = 27, EV_SLOT = 28, EV_END = 29;
__device__ __forceinline__ uint32_t ev_bar(uint32_t bars, int e) { return bars + 8 * (BAR_EV + e); }
__device__ __forceinline__ uint32_t full_bar(uint32_t bars, int j) { return bars + 8 * (BAR_FULL + j); }
constexpr unsigned long long STAGES = 0xb4b4924924924ull;
__host__ __device__ constexpr int b_x(int t) { return ((0xb2c1430bu >> (4 * t)) & 15) * 2; }
__host__ __device__ constexpr int b_w(int t) { return (0x0d0a120eu >> (8 * (t & 3))) & 31; }
__host__ __device__ constexpr int b_ws(int t) { return (t & 3) == 3 ? 4 : 1; }

struct Scratch {
  uint4 cw[CW_BYTES / 16];
  uint2 part[8 * NB];
  unsigned epoch[GRID];
  unsigned foldflag;
};
__device__ __align__(128) Scratch g_scratch;
__device__ __align__(1024) __nv_bfloat16 g_x0[NB * FS * 64];
struct GPtr { Scratch* s; const uint4* tab; uint32_t zero; };

__device__ __forceinline__ void wg_fence() { asm volatile("wgmma.fence.sync.aligned;" ::: "memory"); }
__device__ __forceinline__ void wg_commit() { asm volatile("wgmma.commit_group.sync.aligned;" ::: "memory"); }
template <int N> __device__ __forceinline__ void wg_wait() { asm volatile("wgmma.wait_group.sync.aligned %0;" ::"n"(N) : "memory"); }
__device__ __forceinline__ uint64_t mkdesc(uint32_t addr, uint32_t lbo, uint32_t sbo, uint32_t swz) {
  return (uint64_t)((addr & 0x3FFFF) >> 4) | ((uint64_t)(lbo >> 4) << 16) | ((uint64_t)(sbo >> 4) << 32) | ((uint64_t)swz << 62);
}
__device__ __forceinline__ bool elect1() {
  uint32_t p; asm volatile("{\n.reg .pred p;\nelect.sync _|p, 0xffffffff;\nselp.b32 %0, 1, 0, p;\n}" : "=r"(p)); return p;
}
__device__ __forceinline__ int fresh(int v) { asm volatile("" : "+r"(v)); return v; }
__device__ __forceinline__ void mbar_init(uint32_t bar, uint32_t cnt) { asm volatile("mbarrier.init.shared::cta.b64 [%0], %1;" ::"r"(bar), "r"(cnt) : "memory"); }
__device__ __forceinline__ void mbar_arrive(uint32_t bar) { asm volatile("mbarrier.arrive.shared::cta.b64 _, [%0];" ::"r"(bar) : "memory"); }
__device__ __forceinline__ void mbar_arrive_cta(uint32_t bar, uint32_t cta) {
  asm volatile("{\n.reg .b32 r;\nmapa.shared::cluster.u32 r, %0, %1;\nmbarrier.arrive.shared::cluster.b64 _, [r];\n}" ::"r"(bar), "r"(cta) : "memory");
}
__device__ __forceinline__ void mbar_expect_tx(uint32_t bar, uint32_t bytes) { asm volatile("mbarrier.arrive.expect_tx.shared::cta.b64 _, [%0], %1;" ::"r"(bar), "r"(bytes) : "memory"); }
__device__ __forceinline__ void mbar_wait(uint32_t bar, uint32_t parity) {
  asm volatile("{\n.reg .pred p;\nLAB_WAIT:\n"
               "mbarrier.try_wait.parity.shared::cta.b64 p, [%0], %1;\n"
               "@!p bra LAB_WAIT;\n}" ::"r"(bar), "r"(parity) : "memory");
}
__device__ __forceinline__ void flag_wait(const unsigned* p, unsigned target, unsigned sleep_ns) {
  asm volatile("{\n.reg .pred p;\n.reg .u32 n, v;\nmov.u32 n, 0;\nLAB_WAIT:\n"
               "ld.acquire.gpu.global.u32 v, [%0];\n"
               "sub.u32 v, v, %1;\n"
               "setp.ge.s32 p, v, 0;\n"
               "@p bra DONE;\n"
               "nanosleep.u32 %2;\n"
               "add.u32 n, n, 1;\n"
               "setp.lt.u32 p, n, 400000;\n"
               "@p bra LAB_WAIT;\n"
               "DONE:\n}" ::"l"(p), "r"(target), "r"(sleep_ns) : "memory");
}
__device__ __forceinline__ void put_tagged(uint2* p, float v, unsigned tag) {
  asm volatile("st.relaxed.gpu.global.v2.b32 [%0], {%1, %2};" ::"l"(p), "r"(__float_as_uint(v)), "r"(tag) : "memory");
}
__device__ __forceinline__ void flag_add(unsigned* p) { asm volatile("red.release.gpu.global.add.u32 [%0], 1;" ::"l"(p) : "memory"); }
__device__ __forceinline__ void tma_load(uint32_t dst, const CUtensorMap* tm, int c0, int c1, uint32_t bar) {
  asm volatile("cp.async.bulk.tensor.2d.shared::cluster.global.mbarrier::complete_tx::bytes [%0], [%1, {%3, %4}], [%2];"
               ::"r"(dst), "l"(tm), "r"(bar), "r"(c0), "r"(c1) : "memory");
}
__device__ __forceinline__ void tma_row_mc(uint32_t dst, const CUtensorMap* tm, int row, uint32_t bar) {
  asm volatile("cp.async.bulk.tensor.2d.shared::cluster.global.mbarrier::complete_tx::bytes.multicast::cluster [%0], [%1, {%3, %4}], [%2], %5;"
               ::"r"(dst), "l"(tm), "r"(bar), "r"(0), "r"(row), "h"((uint16_t)3));
}
__device__ __forceinline__ void tma_row(uint32_t dst, const CUtensorMap* tm, int row, uint32_t bar) {
  asm volatile("cp.async.bulk.tensor.2d.shared::cluster.global.mbarrier::complete_tx::bytes [%0], [%1, {%3, %4}], [%2];"
               ::"r"(dst), "l"(tm), "r"(bar), "r"(0), "r"(row));
}
__device__ __forceinline__ void tma_store(const CUtensorMap* tm, int c0, int c1, uint32_t src) {
  asm volatile("cp.async.bulk.tensor.2d.global.shared::cta.bulk_group [%0, {%1, %2}], [%3];\ncp.async.bulk.commit_group;"
               ::"l"(tm), "r"(c0), "r"(c1), "r"(src) : "memory");
}
template <int N> __device__ __forceinline__ void store_read() { asm volatile("cp.async.bulk.wait_group.read %0;" ::"n"(N) : "memory"); }
__device__ __forceinline__ void bulk_load(uint32_t dst, const void* src, uint32_t bytes, uint32_t bar) {
  asm volatile("cp.async.bulk.shared::cluster.global.mbarrier::complete_tx::bytes [%0], [%1], %2, [%3];"
               ::"r"(dst), "l"(src), "r"(bytes), "r"(bar));
}
__device__ __forceinline__ void l2_prefetch(const void* src, uint32_t bytes) {
  asm volatile("cp.async.bulk.prefetch.L2.global [%0], %1;" ::"l"(src), "r"(bytes));
}
__device__ __forceinline__ void w_prefetch(const __nv_bfloat16* w1, int f, int cta, int piece) {
  l2_prefetch(w1 + (f * 64 + (cta >> 3) * 4 + (cta & 1) * 2 + (piece & 1)) * DIN + (piece < 2 ? (cta & 6) * 192 : 1536 + (cta & 4) * 16),
              piece < 2 ? 768 : 128);
}
__device__ __forceinline__ void cpasync16(uint32_t dst, const void* src) {
  asm volatile("cp.async.cg.shared.global [%0], [%1], 16;" ::"r"(dst), "l"(src) : "memory");
}
template <int ID, int N> __device__ __forceinline__ void bar_sync() { asm volatile("bar.sync %0, %1;" ::"n"(ID), "n"(N) : "memory"); }
template <int ID, int N> __device__ __forceinline__ void bar_arrive() { asm volatile("bar.arrive %0, %1;" ::"n"(ID), "n"(N) : "memory"); }
__device__ __forceinline__ void ldsm4t(uint32_t& a, uint32_t& b, uint32_t& c, uint32_t& d, uint32_t addr) {
  asm volatile("ldmatrix.sync.aligned.m8n8.x4.trans.shared.b16 {%0,%1,%2,%3}, [%4];" : "=r"(a), "=r"(b), "=r"(c), "=r"(d) : "r"(addr) : "memory");
}
__device__ __forceinline__ int lds32(uint32_t addr) { int v; asm volatile("ld.shared.b32 %0, [%1];" : "=r"(v) : "r"(addr)); return v; }
__device__ __forceinline__ int2 lds64(uint32_t addr) { int2 v; asm volatile("ld.shared.v2.b32 {%0,%1}, [%2];" : "=r"(v.x), "=r"(v.y) : "r"(addr)); return v; }
__device__ __forceinline__ int4 lds128(uint32_t addr) {
  int4 v; asm volatile("ld.shared.v4.b32 {%0,%1,%2,%3}, [%4];" : "=r"(v.x), "=r"(v.y), "=r"(v.z), "=r"(v.w) : "r"(addr)); return v;
}
__device__ __forceinline__ float4 lds128f(uint32_t addr) {
  float4 v; asm volatile("ld.shared.v4.f32 {%0,%1,%2,%3}, [%4];" : "=f"(v.x), "=f"(v.y), "=f"(v.z), "=f"(v.w) : "r"(addr) : "memory"); return v;
}
__device__ __forceinline__ float4 lds128f(uint32_t addr, uint32_t off) {
  float4 v;
  asm volatile("{\n.reg .u32 t;\nadd.u32 t, %4, %5;\nld.shared.v4.f32 {%0,%1,%2,%3}, [t];\n}" : "=f"(v.x), "=f"(v.y), "=f"(v.z), "=f"(v.w) : "r"(addr), "r"(off) : "memory");
  return v;
}
__device__ __forceinline__ void sts32f(uint32_t addr, float v) { asm volatile("st.shared.f32 [%0], %1;" ::"r"(addr), "f"(v) : "memory"); }
__device__ __forceinline__ float bf_lo(uint32_t v) { return __uint_as_float(v << 16); }
__device__ __forceinline__ float bf_hi(uint32_t v) { return __uint_as_float(v & 0xffff0000u); }
__device__ __forceinline__ float bf2f(__nv_bfloat16 v) { return __bfloat162float(v); }

__device__ __forceinline__ uint32_t mul2(uint32_t a, uint32_t b) {
  uint32_t r; asm volatile("mul.rn.bf16x2 %0, %1, %2;" : "=r"(r) : "r"(a), "r"(b)); return r;
}
__device__ __forceinline__ uint32_t mul2lo(uint32_t a, uint32_t b) {
  uint32_t r;
  asm volatile("{\n.reg .b16 l, h;\n.reg .b32 t;\nmov.b32 {l, h}, %2;\nmov.b32 t, {l, l};\nmul.rn.bf16x2 %0, %1, t;\n}" : "=r"(r) : "r"(a), "r"(b));
  return r;
}
__device__ __forceinline__ uint32_t mul2hi(uint32_t a, uint32_t b) {
  uint32_t r;
  asm volatile("{\n.reg .b16 l, h;\n.reg .b32 t;\nmov.b32 {l, h}, %2;\nmov.b32 t, {h, h};\nmul.rn.bf16x2 %0, %1, t;\n}" : "=r"(r) : "r"(a), "r"(b));
  return r;
}

__host__ __device__ constexpr int xfield(int r, int e, int c) {
  return r == 9 ? 24 + e : 8 * (r / 3) + 2 * (((r % 3) + c) & 3) + (((r % 3) == 2 && c >= 2) ? 1 - e : e);
}
__host__ __device__ constexpr int blk_a(int b) { return b < 12 ? 3 * (b / 8) + ((b & 3) == 3) : (b < 15 ? 3 * (b - 12) : 3 * (b - 15)); }
__host__ __device__ constexpr int blk_b(int b) { return b < 12 ? 3 * (b < 4 ? 1 : 2) + ((b & 3) == 3 ? 0 : (b & 3)) : (b < 15 ? 3 * (b - 12) + 1 : 9); }
__host__ __device__ constexpr int slot_pq(int u, int e, int c) {
  return u < 36 ? (xfield(blk_a(u >> 1), e, c) | (xfield(blk_b(u >> 1), u & 1, c) << 8))
       : u < 39 ? (xfield(3 * (u - 36), e, c) * 257)
       : u < 42 ? (xfield(3 * (u - 39), e, c) | (xfield(3 * (u - 39) + 2, e, c) << 8))
       : u == 42 ? (xfield(3 * e, 0, c) | (xfield(3 * e, 1, c) << 8))
       : u == 43 ? (e == 0 ? (xfield(6, 0, c) | (xfield(6, 1, c) << 8))
                           : (c == 0 ? 24 * 257 : c == 1 ? 25 * 257 : c == 2 ? (24 | 25 << 8) : 26 * 257))
       : u < 47 ? (xfield(3 * (u - 44), e, c) | (26 << 8))
       : (c == 0 ? ((24 + e) | 26 << 8) : 27 * 257);
}
struct SlotTab { uint32_t v[48 * 8]; };
constexpr SlotTab make_slot_tab() {
  SlotTab t{};
  for (int u = 0; u < 48; u++)
    for (int k = 0; k < 8; k++) {
      const int pq = slot_pq(u, k & 1, k >> 1), p = pq & 255, q = pq >> 8;
      t.v[u * 8 + k] = (uint32_t)((p * 28 + q) * 4) | ((uint32_t)(((p != q && q < 26) ? q * 28 + p : 27 * 28 + 27) * 4) << 16);
    }
  return t;
}
__device__ __align__(16) const SlotTab g_slot_tab = make_slot_tab();

struct CinCtx {
  uint32_t o03, o14, o25, o69, o78, cin, selA, selB;
  bool ones, lead;
  uint32_t so, so2, co, co2, bar, jump, dslot, last;
  bool ring;
};
constexpr unsigned long long CW_DESC = (unsigned long long)((SMEM_BASE + OFF_CW) >> 4) | (8ull << 16) | (16ull << 32);
constexpr unsigned long long CWL_DESC = CW_DESC + (OFF_CWL - OFF_CW) / 16;

template <int U>
__device__ __forceinline__ uint32_t zreg(const uint32_t (&x)[10][2], int h, const CinCtx& c) {
  if constexpr (U < 36) {
    if constexpr (U & 1) return mul2hi(x[blk_a(U >> 1)][h], x[blk_b(U >> 1)][h]);
    else return mul2lo(x[blk_a(U >> 1)][h], x[blk_b(U >> 1)][h]);
  } else if constexpr (U < 39) {
    return mul2(x[3 * (U - 36)][h], x[3 * (U - 36)][h]);
  } else if constexpr (U < 42) {
    return mul2(x[3 * (U - 39)][h], x[3 * (U - 39) + 2][h]);
  } else if constexpr (U == 42) {
    return mul2(__byte_perm(x[0][h], x[3][h], 0x5410), __byte_perm(x[0][h], x[3][h], 0x7632));
  } else {
    const uint32_t f = c.ones ? 0x3f803f80u : x[9][h];
    return mul2(__byte_perm(x[6][h], f, c.selA), __byte_perm(x[6][h], f, c.selB));
  }
}

template <int G>
__device__ __forceinline__ void z_fill(uint32_t (&z)[8], const uint32_t (&x)[10][2], const CinCtx& c) {
  z[0] = zreg<4 * G>(x, 0, c);     z[1] = zreg<4 * G>(x, 1, c);
  z[2] = zreg<4 * G + 1>(x, 0, c); z[3] = zreg<4 * G + 1>(x, 1, c);
  z[4] = zreg<4 * G + 2>(x, 0, c); z[5] = zreg<4 * G + 2>(x, 1, c);
  z[6] = zreg<4 * G + 3>(x, 0, c); z[7] = zreg<4 * G + 3>(x, 1, c);
}
__host__ __device__ constexpr unsigned long long cw_desc(int s) { return CW_DESC + (s < CW_CUT ? s * 1792 : OFF_CW2 - OFF_CW + (s - CW_CUT) * 1792) / 16; }
template <int G>
__device__ __forceinline__ void z_mma(float (&acc)[28], const uint32_t (&z)[8]) {
  wgmma_rs_n56<cw_desc(2 * G), G != 0>(acc, z[0], z[1], z[2], z[3]);
  wgmma_rs_n56<cw_desc(2 * G + 1), 1>(acc, z[4], z[5], z[6], z[7]);
}

__device__ __forceinline__ void cin_finish(const CinCtx& c, float (&acc)[28], uint32_t out) {
#pragma unroll
  for (int i = 0; i < 28; i++) asm volatile("" : "+f"(acc[i]));
  float s0 = acc[12] * acc[13], s1 = acc[14] * acc[15];
#pragma unroll
  for (int i = 0; i < 12; i += 2) {
    s0 = fmaf(acc[i], acc[16 + i], s0);
    s1 = fmaf(acc[i + 1], acc[17 + i], s1);
  }
  sts32f(c.cin + out, s0 + s1);
}

__device__ __forceinline__ void cin_ldsm(const CinCtx& c, uint32_t so, uint32_t (&x)[10][2]) {
  ldsm4t(x[0][0], x[0][1], x[3][0], x[3][1], so + c.o03);
  ldsm4t(x[1][0], x[1][1], x[4][0], x[4][1], so + c.o14);
  ldsm4t(x[2][0], x[2][1], x[5][0], x[5][1], so + c.o25);
  ldsm4t(x[6][0], x[6][1], x[9][0], x[9][1], so + c.o69);
  ldsm4t(x[7][0], x[7][1], x[8][0], x[8][1], so + c.o78);
}
__device__ __forceinline__ void cin_load(const CinCtx& c, int k, bool real, uint32_t (&x)[10][2]) {
  if (k == 0 && real) mbar_wait(c.bar, 0);
  cin_ldsm(c, k ? c.so2 : c.so, x);
  if (k == 1 && c.lead) mbar_arrive(c.bar + 8 * NPAIR);
}
__device__ __forceinline__ void cin_advance(CinCtx& c) {
  const uint32_t d = c.so == c.jump ? c.dslot : 2 * XSLOT;
  c.so += d; c.so2 += d;
  c.co = c.ring ? c.co + 2 * CROW : c.so;
  c.bar += 8;
}
constexpr int CG_WAIT = 3;
constexpr int CG_FIN = 3;
constexpr int CG_HEAD = 4;
constexpr int CG_LIN = 5;
constexpr int CG_LOAD = 5;
constexpr int CG_N = 11;
static_assert(CG_FIN >= CG_WAIT && CG_FIN < CG_HEAD && CG_LOAD >= CG_HEAD && CG_LIN >= CG_HEAD && CG_LOAD < 10, "CIN schedule");
template <int G, int GEND, typename F>
__device__ __forceinline__ void cin_groups(const CinCtx& c, const uint32_t (&x)[10][2], float (&acc)[28], uint32_t (&z)[8],
                                           int q, bool more, uint32_t (&xn)[10][2], F finish) {
  if constexpr (G < GEND) {
    wg_fence();
    if constexpr (G == CG_LIN) {
      wgmma_rs_n32<CWL_DESC, 1>(acc, x[0][0], x[0][1], x[3][0], x[3][1]);
      wgmma_rs_n32<CWL_DESC + 1024 / 16, 1>(acc, x[6][0], x[6][1], x[9][0], x[9][1]);
    }
    z_mma<G>(acc, z);
    wg_commit();
    if constexpr (G == CG_LOAD) cin_load(c, q, more, xn);
    uint32_t zn[8];
    if constexpr (G + 1 < CG_N) z_fill<G + 1>(zn, x, c); else z_fill<0>(zn, xn, c);
    if constexpr (G == CG_FIN) finish();
    wg_wait<CG_WAIT>();
    if constexpr (G + 1 < GEND) cin_groups<G + 1, GEND>(c, x, acc, zn, q, more, xn, finish);
    else {
#pragma unroll
      for (int i = 0; i < 8; i++) z[i] = zn[i];
    }
    if constexpr (G + 1 < GEND) {
#pragma unroll
      for (int i = 0; i < 8; i++) z[i] = zn[i];
    }
  }
}
template <typename F>
__device__ __forceinline__ void cin_head(const CinCtx& c, uint32_t (&x)[10][2], float (&acc)[28], uint32_t (&z)[8], F finish) {
  cin_groups<0, CG_HEAD>(c, x, acc, z, 0, false, x, finish);
}
__device__ __forceinline__ void cin_tail(const CinCtx& c, const uint32_t (&x)[10][2], float (&acc)[28], uint32_t (&z)[8],
                                         int q, bool more, uint32_t (&xn)[10][2]) {
  cin_groups<CG_HEAD, CG_N>(c, x, acc, z, q, more, xn, []() {});
}

__device__ __forceinline__ int slot_of(int wg, int j) {
  return wg ? (j == 0 ? 9 * UNIT + XSLOT : j <= 8 ? 2 * UNIT + (j - 1) * XSLOT : 21 * UNIT + (j - 9) * XSLOT)
            : (j < 3 ? OFF_GIDX + j * XSLOT : 14 * UNIT + (j - 3) * XSLOT);
}

__device__ __forceinline__ void cin_begin(CinCtx& c, uint32_t sb, int wg, uint32_t first, uint32_t (&x)[10][2], float (&acc)[28], uint32_t (&z)[8]) {
  int t; asm volatile("mov.u32 %0, %%tid.x;" : "=r"(t));
  const int m = t & 16, f0 = t & 7, f1 = (f0 + 2) & 7, f2 = (f0 ^ 4) ^ (f0 >> 2);
  const uint32_t base = sb + m * 64, ch = (t & 96) + (t & 8) * 2;
  c.o03 = (base + f0 * 0x90) ^ ch;
  c.o14 = (base + f1 * 0x90) ^ ch;
  c.o25 = (base + f2 * 0x90) ^ ch;
  c.o69 = (base + 2048 + (m ? f0 & 1 : f0) * 0x90) ^ ch;
  c.o78 = m ? c.o25 + 1024 : c.o14 + 2048;
  mbar_wait(sb + OFF_BAR + 8 * BAR_GDONE, 0);
  mbar_wait(sb + OFF_BAR + 8 * (BAR_C0 + wg), 0);
  cin_ldsm(c, first, x);
  mbar_wait(sb + OFF_BAR + 8 * BAR_CW, 0);
  z_fill<0>(z, x, c);
  cin_head(c, x, acc, z, []() {});
}
__device__ __forceinline__ void cin_setup(CinCtx& c, uint32_t sb, int wg, int p, bool gemm, int nj, uint32_t zero) {
  c.bar = sb + (gemm ? OFF_BAR + 8 * (BAR_CFULL + wg * 8) : XOFF_BAR + wg * 16 * NPAIR);
  c.lead = (p & 31) == 0 && !gemm; c.ring = !gemm;
  c.so = !gemm ? XOFF_SLOT + 8 * wg * XSLOT : wg ? 2 * UNIT : OFF_GIDX + XSLOT;
  c.jump = c.so + (gemm && !wg ? 0 : 6 * XSLOT);
  c.dslot = !gemm ? -6 * XSLOT : wg ? 19 * UNIT - 6 * XSLOT : 14 * UNIT - OFF_GIDX - XSLOT;
  c.co = gemm ? c.so : (wg ? XOFF_CIN1 : XOFF_CIN0) - NF * 128;
  c.co2 = gemm ? XSLOT : CROW;
  c.so2 = c.so + XSLOT + zero;
  c.last = gemm ? slot_of(wg, (nj - 1) | 1) : c.co + ((nj - 1) & ~1) * CROW;
  c.cin = sb + NF * 128 + p * 4;
  const int q = p & 3;
  c.selA = q == 1 ? 0x7610 : 0x5410;
  c.selB = q == 0 ? 0x5432 : 0x7632;
  c.ones = q == 3;
}
template <typename F2, typename F3>
__device__ __forceinline__ void cin_run(CinCtx& c, int nj, uint32_t (&xA)[10][2], float (&accA)[28], uint32_t (&z)[8], F2 before_end, F3 st5) {
  float accB[28];
  uint32_t xB[10][2];
  const uint32_t lastA = nj & 1 ? c.last : 0;
#pragma unroll 1
  for (int j = 0;; j += 2) {
    cin_tail(c, xA, accA, z, 0, c.co != lastA, xB);
    if (c.co == lastA) { before_end(); wg_wait<0>(); cin_finish(c, accA, c.co); break; }
    cin_head(c, xB, accB, z, [&]() { st5(j); cin_finish(c, accA, c.co); });
    cin_tail(c, xB, accB, z, 1, true, xA);
    if (c.co == c.last) { before_end(); wg_wait<0>(); cin_finish(c, accB, c.co + c.co2); break; }
    cin_head(c, xA, accA, z, [&]() { st5(j + 1); cin_finish(c, accB, c.co + c.co2); });
    cin_advance(c);
  }
}

constexpr float ALPHA = 0.3292034911525734f, KAPPA = 2.423681954311584f;
__device__ __forceinline__ float gelu_acc(float v, float ab, float w, float s, float alpha = ALPHA) {
  const float a = fmaf(v, alpha, ab);
  const float u = a * fmaf(a, a, KAPPA);
  float th; asm("tanh.approx.f32 %0, %1;" : "=f"(th) : "f"(u));
  return fmaf(fmaf(a, th, a), w, s);
}

constexpr int QD = 2;
template <int NG>
struct Gelu {
  float4 q[QD + 1];
  uint32_t ep;
  __device__ __forceinline__ void start(uint32_t a) {
    ep = a;
#pragma unroll
    for (int i = 0; i < QD; i++) q[i] = lds128f(ep + i * 64);
  }
  template <int I0, int I1>
  __device__ __forceinline__ void part(float (&d)[4 * NG], float& r0, float& r1, uint32_t done) {
    float alpha;
    asm volatile("{\n.reg .pred p;\nmbarrier.test_wait.parity.shared::cta.b64 p, [%1], 0;\nselp.f32 %0, %2, 0f7FC00000, p;\n}"
                 : "=f"(alpha) : "r"(done), "f"(ALPHA) : "memory");
    part<I0, I1>(d, r0, r1, alpha);
  }
  template <int I0, int I1>
  __device__ __forceinline__ void part(float (&d)[4 * NG], float& r0, float& r1, float alpha = ALPHA) {
#pragma unroll
    for (int i = I0; i < I1; i++) {
      if (i + QD < NG) q[(i + QD) % (QD + 1)] = lds128f(ep + (i + QD) * 64);
      const float4 v = q[i % (QD + 1)];
#pragma unroll
      for (int e = 0; e < 4; e++) asm volatile("" : "+f"(d[4 * i + e]));
      const float al = i < I0 + QD ? alpha : ALPHA;
      r0 = gelu_acc(d[4 * i + 0], v.x, v.z, r0, al);
      r0 = gelu_acc(d[4 * i + 1], v.y, v.w, r0, al);
      r1 = gelu_acc(d[4 * i + 2], v.x, v.z, r1, al);
      r1 = gelu_acc(d[4 * i + 3], v.y, v.w, r1, al);
    }
    asm volatile("" : "+f"(r0), "+f"(r1));
  }
};
__device__ __forceinline__ float quad_sum(float r0, float r1, float r2, float r3, int lane) {
  const bool b0 = lane & 1, b1 = lane & 2;
  const float a = (b0 ? r1 : r0) + __shfl_xor_sync(0xffffffffu, b0 ? r0 : r1, 1);
  const float b = (b0 ? r3 : r2) + __shfl_xor_sync(0xffffffffu, b0 ? r2 : r3, 1);
  return (b1 ? b : a) + __shfl_xor_sync(0xffffffffu, b1 ? a : b, 2);
}
__device__ __forceinline__ void sts128f(uint32_t addr, float a, float b, float c, float d) {
  asm volatile("st.shared.v4.f32 [%0], {%1, %2, %3, %4};" ::"r"(addr), "f"(a), "f"(b), "f"(c), "f"(d) : "memory");
}
__device__ __forceinline__ void pin(float a, float b, uint32_t addr, uint32_t zero) {
  asm volatile("{\n.reg .pred p;\nsetp.ne.u32 p, %3, 0;\n@p st.shared.v2.f32 [%0], {%1, %2};\n}" ::"r"(addr), "f"(a), "f"(b), "r"(zero) : "memory");
}
__device__ __forceinline__ void hand_on(float (&d)[96], const float (&s)[96]) {
#pragma unroll
  for (int i = 0; i < 96; i++) asm volatile("mov.b32 %0, %1;" : "=f"(d[i]) : "f"(s[i]));
}
__device__ __forceinline__ uint64_t desc_x(int u) { return mkdesc(SMEM_BASE, 16, 1024, 1) + u * (UNIT / 16); }
__device__ __forceinline__ uint64_t desc_w(int u, int stride = 1) { return mkdesc(SMEM_BASE, stride * UNIT, 1024, 1) + u * (UNIT / 16); }
__device__ __forceinline__ void tile_step(float (&d)[96], uint64_t dA, uint64_t dB) {
  wg_fence();
#pragma unroll
  for (int k = 0; k < 4; k++) wgmma_ss_n192(d, dA + 2 * k, dB + 128 * k, 1);
  wg_commit();
}
template <int K0 = 0, int K1 = 4>
__device__ __forceinline__ void wide_step(float (&d)[96], float (&e)[32], uint64_t dA, uint64_t dB) {
  wg_fence();
#pragma unroll
  for (int k = K0; k < K1; k++) wgmma_ss_n256(d, e, dA + 2 * k, dB + 128 * k, 1);
  wg_commit();
}
__device__ __forceinline__ int cin_row(int c, int j) {
  if (c >= NGEMM) {
    const int e = (c - NGEMM) * NC_EXTRA + j;
    c = e < 256 ? e >> 1 : NBIG + e - 256;
    j = e < 256 ? 30 + (e & 1) : 29;
  }
  return (c >> 3) * 256 + (c & 2) * 64 + (c & 1) * 64 + (c & 4) * 8 + j;
}
__device__ __forceinline__ int cin_count(int c) {
  return c < NGEMM ? NC_GEMM + (c < NBIG) : NC_EXTRA;
}

__device__ __forceinline__ int fold_i0(int e) { return e < 2 ? 7 * e : 2 + 6 * e; }
__device__ __forceinline__ uint32_t ldg16(const void* p) { uint16_t v; asm volatile("ld.global.nc.u16 %0, [%1];" : "=h"(v) : "l"(p)); return v; }
__device__ __forceinline__ uint4 ldg128(const void* p) {
  uint4 v; asm volatile("ld.global.nc.v4.u32 {%0,%1,%2,%3}, [%4];" : "=r"(v.x), "=r"(v.y), "=r"(v.z), "=r"(v.w) : "l"(p)); return v;
}
__device__ __forceinline__ void sts64f(uint32_t addr, float a, float b) { asm volatile("st.shared.v2.f32 [%0], {%1, %2};" ::"r"(addr), "f"(a), "f"(b) : "memory"); }
__device__ __forceinline__ float to_tf32(float v) { uint32_t r; asm("cvt.rna.tf32.f32 %0, %1;" : "=r"(r) : "f"(v)); return __uint_as_float(r); }
__device__ __forceinline__ uint4 fold_chunk(uint32_t base, const uint4 t0, const uint4 t1) {
  const uint32_t t[8] = {t0.x, t0.y, t0.z, t0.w, t1.x, t1.y, t1.z, t1.w};
  uint32_t v[4];
#pragma unroll
  for (int c = 0; c < 4; c++) {
    const float w0 = __int_as_float(lds32(base + (t[2 * c] & 0xffff))) + __int_as_float(lds32(base + (t[2 * c] >> 16)));
    const float w1 = __int_as_float(lds32(base + (t[2 * c + 1] & 0xffff))) + __int_as_float(lds32(base + (t[2 * c + 1] >> 16)));
    __nv_bfloat162 pk = __floats2bfloat162_rn(w0, w1);
    v[c] = *reinterpret_cast<uint32_t*>(&pk);
  }
  return make_uint4(v[0], v[1], v[2], v[3]);
}
__device__ __forceinline__ int cw_chunk(int u, int n) {
  return ((u < 44 ? (u >> 1) * 1792 : CW_MAIN + ((u - 44) >> 1) * 1024) + (n >> 3) * 256 + (u & 1) * 128 + (n & 7) * 16) >> 4;
}
__device__ __forceinline__ void fold_weights(uint8_t* smem, uint32_t sb, int e, const __nv_bfloat16* __restrict__ wco, const GPtr gp) {
  const int tid = threadIdx.x, lane = tid & 31, warp = tid >> 5;
  const uint32_t bars = sb + OFF_BAR;
  const int i0 = fold_i0(e), i = i0 + warp;
  const bool own = i < fold_i0(e + 1);
  const uint32_t wb16 = ldg16(wco + (lane < NF ? 26 + lane : 0)), wc16 = ldg16(wco + (lane < NF ? 52 + lane : 0));
  const uint32_t w116 = ldg16(wco + (own ? i : 0));
  const uint4* tab = gp.tab;
  const uint4 ta0 = ldg128(tab + 2 * lane), ta1 = ldg128(tab + 2 * lane + 1);
  const uint4 tb0 = ldg128(tab + 64 + 2 * (lane & 15)), tb1 = ldg128(tab + 65 + 2 * (lane & 15));
  asm volatile("barrier.cluster.arrive.relaxed.aligned;\nbarrier.cluster.wait.acquire.aligned;" ::: "memory");
  if (warp >= 6) {
    for (int t = tid - 192; t < 6 * 20; t += 64) sts64f(sb + XOFF_M + 26 * 160 + t * 8, 0.f, 0.f);
    if (warp == 6 && lane < NF) {
      sts64f(sb + XOFF_M + lane * 160 + 104, bf_lo(wb16), 0.f);
      sts64f(sb + XOFF_M + lane * 160 + 112, 0.f, 0.f);
      sts64f(sb + XOFF_M + lane * 160 + 120, 0.f, 0.f);
    }
    if (warp == 7) {
      gp.s->cw[cw_chunk(lane, 28 + e)] = make_uint4(0, 0, 0, 0);
      if (lane < 16) gp.s->cw[cw_chunk(32 + lane, 28 + e)] = make_uint4(0, 0, 0, 0);
    }
  } else {
    mbar_wait(bars + 8 * BAR_GIDX, 0);
    float m0 = 0.f, m1 = 0.f, m2 = 0.f, m3 = 0.f;
    const uint32_t a = sb + XOFF_W3 + (tid < 169 ? tid : 0) * 8;
#pragma unroll 2
    for (int g = 0; g < NF; g++) {
      const int2 v = lds64(a + g * 1352);
      const float w = __shfl_sync(0xffffffffu, bf_lo(wc16), g);
      m0 = fmaf(w, bf_lo(v.x), m0); m1 = fmaf(w, bf_hi(v.x), m1);
      m2 = fmaf(w, bf_lo(v.y), m2); m3 = fmaf(w, bf_hi(v.y), m3);
    }
    if (tid < 169) {
      const int o = tid * 2, o2 = o + 1;
      sts64f(sb + XOFF_M + (o / 13) * 160 + (o % 13) * 8, to_tf32(m0), to_tf32(m1));
      sts64f(sb + XOFF_M + (o2 / 13) * 160 + (o2 % 13) * 8, to_tf32(m2), to_tf32(m3));
    }
  }
  const uint32_t sT = sb + XOFF_S + warp * 2 * 3136, sA = sT + 3136;
  const int g = lane >> 2, c = lane & 3;
  uint32_t af[2][8];
  mbar_wait(bars + 8 * BAR_FULL, 0);
  if (own) {
#pragma unroll
    for (int k = 0; k < 8; k++) {
      const int h = 4 * k + c;
      const uint32_t a = sb + XOFF_W2 + ((h < NF ? h : 0) * 676 + i * 26 + 2 * g) * 2;
      af[0][k] = lds32(a);
      af[1][k] = lds32(a + (g < 5 ? 32 : 0));
    }
#pragma unroll 1
    for (int o = lane; o < 338; o += 32) {
      const uint32_t v = lds32(sb + XOFF_W1 + (i - (i0 & ~1)) * 1352 + o * 4);
      sts64f(sA + (o / 13) * 112 + (o % 13) * 8, bf_lo(v), bf_hi(v));
    }
    if (lane < 28) sts64f(sA + lane * 112 + 104, 0.f, 0.f);
    if (lane < 2) sts64f(sT + (26 + lane) * 112 + 104, lane == 0 ? bf_lo(w116) : 0.f, 0.f);
  }
  bar_sync<4, 256>();
  if (own) {
#pragma unroll 1
    for (int n = 0; n < 4; n++) {
      float d[2][4] = {};
#pragma unroll
      for (int ks = 0; ks < 4; ks++) {
        const uint32_t b0 = lds32(sb + XOFF_M + (8 * ks + c) * 160 + (8 * n + g) * 4);
        const uint32_t b1 = lds32(sb + XOFF_M + (8 * ks + c + 4) * 160 + (8 * n + g) * 4);
#pragma unroll
        for (int m = 0; m < 2; m++)
          asm volatile("mma.sync.aligned.m16n8k8.row.col.f32.tf32.tf32.f32 {%0,%1,%2,%3}, {%4,%5,%6,%7}, {%8,%9}, {%0,%1,%2,%3};"
                       : "+f"(d[m][0]), "+f"(d[m][1]), "+f"(d[m][2]), "+f"(d[m][3])
                       : "r"(af[m][2 * ks] << 16), "r"(af[m][2 * ks] & 0xffff0000u), "r"(af[m][2 * ks + 1] << 16),
                         "r"(af[m][2 * ks + 1] & 0xffff0000u), "r"(b0), "r"(b1));
      }
      if (n < 3 || c < 2) {
        const uint32_t a = sT + 2 * g * 112 + (8 * n + 2 * c) * 4;
        sts64f(a, d[0][0], d[0][1]);
        sts64f(a + 112, d[0][2], d[0][3]);
        if (g < 5) {
          sts64f(a + 16 * 112, d[1][0], d[1][1]);
          sts64f(a + 17 * 112, d[1][2], d[1][3]);
        }
      }
    }
    __syncwarp();
    const int nt = i < 24 ? i : 2 * i - 24, na = i < 24 ? 32 + i : 2 * i - 23;
#pragma unroll 1
    for (int k = 0; k < 3; k++) {
      const bool isa = k == 1 || (k == 2 && lane >= 16);
      const uint4 v = fold_chunk(isa ? sA : sT, k < 2 ? ta0 : tb0, k < 2 ? ta1 : tb1);
      if (k < 2 || lane < 28 || na < 32) gp.s->cw[cw_chunk(k < 2 ? lane : 32 + (lane & 15), isa ? na : nt)] = v;
    }
  }
  __syncwarp();
  if (lane == 0) flag_add(&gp.s->foldflag);
  bar_sync<4, 256>();
  mbar_wait(bars + 8 * BAR_GDONE, 0);
  if (tid >= 128 && tid < 132) mbar_arrive(ev_bar(bars, EV_END));
}

__global__ void __cluster_dims__(2, 1, 1) __launch_bounds__(384, 1)
xdeepfm_kernel(const int* __restrict__ idx, const __nv_bfloat16* __restrict__ table, const __nv_bfloat16* __restrict__ w1,
               const __nv_bfloat16* __restrict__ b1, const __nv_bfloat16* __restrict__ w2,
               const __nv_bfloat16* __restrict__ ws, const __nv_bfloat16* __restrict__ wco,
               const __nv_bfloat16* __restrict__ bout, __nv_bfloat16* __restrict__ out, const GPtr gp,
               const __grid_constant__ CUtensorMap tmW, const __grid_constant__ CUtensorMap tmT,
               const __grid_constant__ CUtensorMap tmS, const __grid_constant__ CUtensorMap tmC) {
  int myidx, idx1, idx2 = 0, idx3 = 0;
  {
    const int t = threadIdx.x, b = blockIdx.x, half = (b >> 1) ^ (t >= 256 ? t >> 4 : 0);
    const int* ip = idx + (((b >> 3) & 15) * 256 + (half & 1) * 128 + (t < 256 ? t >> 1 : (b & 1) * 64 + ((t >> 1) & 48) + (t & 15))) * NF;
    asm volatile("{\n.reg .pred p;\nsetp.ge.u32 p, %5, 256;\nld.global.nc.v2.s32 {%0, %1}, [%4];\n@p ld.global.nc.v2.s32 {%2, %3}, [%4 + 8];\n}"
                 : "=r"(myidx), "=r"(idx1), "+r"(idx2), "+r"(idx3) : "l"(ip), "r"(t));
  }
  extern __shared__ __align__(1024) uint8_t smem[];
  const uint32_t sb = (uint32_t)__cvta_generic_to_shared(smem);
  const uint32_t bars = sb + OFF_BAR;
  const int tid = threadIdx.x, lane = tid & 31;
  const int warp = __shfl_sync(0xffffffffu, tid >> 5, 0);
  const int cta = blockIdx.x;
  const bool gemm = cta < NGEMM;
  const int nt = cta & 7, rank = cta & 1;

  if (warp == 8 && elect1()) {
    mbar_init(bars + 8 * BAR_GIDX, 1);
    mbar_init(bars + 8 * BAR_FULL, 1);
    mbar_init(bars + 8 * BAR_W0, 1);
    asm volatile("fence.mbarrier_init.release.cluster;" ::: "memory");
    if (gemm) {
      mbar_expect_tx(bars + 8 * BAR_W0, 4 * UNIT);
#pragma unroll
      for (int i = 0; i < 4; i++)
        tma_load(sb + (U_W + i) * UNIT, &tmW, i < 3 ? nt * 192 + i * 64 : 1536 + (nt >> 2) * 64, 0, bars + 8 * BAR_W0);
      mbar_expect_tx(bars + 8 * BAR_FULL, 2 * UNIT);
    } else {
      const int i0 = fold_i0(cta - NGEMM) & ~1, ni = NF - i0 < 8 ? NF - i0 : 8;
      __nanosleep(XD);
      mbar_expect_tx(bars + 8 * BAR_GIDX, 35152);
      bulk_load(sb + XOFF_W3, ws + 2 * 17576, 35152, bars + 8 * BAR_GIDX);
      mbar_expect_tx(bars + 8 * BAR_FULL, 35152 + ni * 1352);
      bulk_load(sb + XOFF_W1, ws + i0 * 676, ni * 1352, bars + 8 * BAR_FULL);
      bulk_load(sb + XOFF_W2, ws + 17576, 35152, bars + 8 * BAR_FULL);
    }
  }
  if (warp < 8 && elect1()) {
#pragma unroll
    for (int i = 0; i < 8; i++) mbar_init(full_bar(bars, 1 + warp * 8 + i), BAR_FULL + 1 + warp * 8 + i < BAR_EV ? 1 : 4);
    asm volatile("fence.mbarrier_init.release.cluster;" ::: "memory");
  }
  if (warp == 7 && lane >= 16 && (lane & 7) < 7) {
    const int l = lane & 7;
    asm volatile("prefetch.global.L2 [%0];" ::"l"(w1 + (((cta >> 3 & 15) * 2 + (cta & 1)) * 2 + ((lane >> 3) & 1)) * DIN + (l < 6 ? (cta & 6) * 192 + l * 64 : 1536 + (cta & 4) * 16)));
  }

  if (warp >= 8) {
    const int pw = warp - 8;
    if (pw && elect1()) {
      if (pw == 1) {
        asm volatile("prefetch.tensormap [%0];" ::"l"(&tmT) : "memory");
        mbar_init(bars + 8 * BAR_CW, 1);
        mbar_init(bars + 8 * BAR_X0, 1);
        mbar_init(bars + 8 * BAR_T, 2);
        mbar_init(bars + 8 * BAR_PARK, 8);
        mbar_init(bars + 8 * BAR_GDONE, 4);
        mbar_init(bars + 8 * BAR_DNN, gemm ? 1 : 4);
      } else {
#pragma unroll
        for (int i = 0; i < 9; i++) mbar_init(bars + 8 * (BAR_C0 + (pw - 2) * 9 + i), 1);
      }
      asm volatile("fence.mbarrier_init.release.cluster;" ::: "memory");
    }
    __syncwarp();
    asm volatile("barrier.cluster.arrive.relaxed.aligned;" ::: "memory");
    asm volatile("barrier.cluster.wait.acquire.aligned;" ::: "memory");
    asm volatile("setmaxnreg.dec.sync.aligned.u32 24;");
    if (gemm) {
      {
        const uint32_t a = sb + OFF_GIDX + ((lane >> 4) * 64 + pw * 16 + (lane & 15)) * NF * 4;
        asm volatile("st.shared.v2.b32 [%0], {%1, %2};\nst.shared.v2.b32 [%0 + 8], {%3, %4};"
                     ::"r"(a), "r"(myidx), "r"(idx1), "r"(idx2), "r"(idx3) : "memory");
        __syncwarp();
      }
      if (elect1()) {
#pragma unroll
        for (int j = 0; j < 16; j += 8) {
          int r[8];
#pragma unroll
          for (int i = 0; i < 8; i++) r[i] = lds32(sb + OFF_GIDX + ((64 + pw * 16 + j + i) * NF) * 4);
#pragma unroll
          for (int i = 0; i < 8; i++) tma_row_mc(sb + U_XB * UNIT + (rank * 64 + pw * 16 + j + i) * 128, &tmT, r[i], bars + 8 * BAR_FULL);
        }
        if (pw == 0) asm volatile("prefetch.tensormap [%0];" ::"l"(&tmS) : "memory");
        int s = 1;
#pragma unroll 1
        for (int fi = 1; fi < NF; fi++) {
          const int f = fresh(fi), pw = fresh(warp) - 8, ct = fresh(cta), nt = ct & 7;
          const int t = f - FS, st = t < 0 ? s : (t & 3) ^ ((t >> 1) & 1), e = f - 3 - (t > 1);
          const uint32_t fb = full_bar(bars, f), ia = sb + OFF_GIDX + (pw * 16 * NF + f) * 4;
          const uint32_t d = sb + (st == 3 ? U_SP : 2 * st) * UNIT + ((ct & 1) * 64 + pw * 16) * 128;
          if (f == 4) mbar_wait(bars + 8 * BAR_GIDX, 0);
          int r[2][RB];
#pragma unroll
          for (int i = 0; i < RB; i++) r[0][i] = lds32(ia + i * NF * 4);
          if (e >= 0) mbar_wait(ev_bar(bars, e), 0);
          if (pw == 0) mbar_expect_tx(fb, t < 0 ? 8 * UNIT : 6 * UNIT);
#pragma unroll
          for (int j = 0; j < 16 / RB; j++) {
#pragma unroll
            for (int i = 0; i < RB; i++) r[(j + 1) & 1][i] = lds32(ia + (RB * j + RB + i + (RB * j + RB >= 16) * 48) * NF * 4);
#pragma unroll
            for (int i = 0; i < RB; i++) tma_row_mc(d + (RB * j + i) * 128, &tmT, r[j & 1][i], fb);
          }
          if (t < 0) {
#pragma unroll
            for (int j = 0; j < 16 / RB; j++) {
              if (j + 1 < 16 / RB) {
#pragma unroll
                for (int i = 0; i < RB; i++) r[(j + 1) & 1][i] = lds32(ia + (64 + RB * j + RB + i) * NF * 4);
              }
#pragma unroll
              for (int i = 0; i < RB; i++) tma_row_mc(d + U_XB * UNIT + (RB * j + i) * 128, &tmT, r[j & 1][i], fb);
            }
          }
          tma_load(sb + (U_W + 4 * st + pw) * UNIT, &tmW, pw < 3 ? nt * 192 + pw * 64 : 1536 + (nt >> 2) * 64, f * 64, fb);
          if (f == GI && pw < 2) {
            if (pw == 0) mbar_expect_tx(bars + 8 * BAR_GIDX, 128 * NF * 4);
            bulk_load(sb + OFF_GIDX + pw * 64 * NF * 4, idx + ((ct >> 3) * 256 + (((ct >> 1) ^ pw) & 1) * 128 + (ct & 1) * 64) * NF, 64 * NF * 4, bars + 8 * BAR_GIDX);
          }
          if (f == GI && pw == 2) asm volatile("prefetch.tensormap [%0];" ::"l"(&tmC) : "memory");
          if (f + WD < NF) w_prefetch(w1, f + WD, ct, pw);
          if (++s == 3) s = 0;
        }
        mbar_wait(bars + 8 * BAR_T, 0);
#pragma unroll 1
        for (int ti = 0; ti < 8; ti++) {
          const int t = fresh(ti), pw = fresh(warp) - 8, e = t < 4 ? 22 - !t : 19 + t;
          const uint32_t ia = sb + OFF_TIDX + t * 256 + pw * 64, fb = full_bar(bars, NF + t);
          const uint32_t d = sb + b_x(t) * UNIT + ((fresh(cta) & 1) * 64 + pw * 16) * 128;
          int4 r[2];
          r[0] = lds128(ia);
          r[1] = lds128(ia + 16);
          mbar_wait(ev_bar(bars, e), 0);
          if (pw == 0) mbar_expect_tx(fb, t < 3 ? 2 * UNIT : 5 * UNIT);
#pragma unroll
          for (int j = 0; j < 4; j++) {
            tma_row_mc(d + (4 * j + 0) * 128, &tmT, r[j & 1].x, fb);
            tma_row_mc(d + (4 * j + 1) * 128, &tmT, r[j & 1].y, fb);
            tma_row_mc(d + (4 * j + 2) * 128, &tmT, r[j & 1].z, fb);
            tma_row_mc(d + (4 * j + 3) * 128, &tmT, r[j & 1].w, fb);
            if (j < 2) r[j & 1] = lds128(ia + 32 + 16 * j);
          }
        }
        mbar_arrive(bars + 8 * BAR_GDONE);
      }
      __syncwarp();
    }
    bar_sync<6, 128>();
    asm volatile("setmaxnreg.inc.sync.aligned.u32 %0;" ::"n"(PREG));
    {
    int cta; asm volatile("mov.u32 %0, %%ctaid.x;" : "=r"(cta));
    int tid; asm volatile("mov.u32 %0, %%tid.x;" : "=r"(tid));
    const int lane = tid & 31, pw = __shfl_sync(0xffffffffu, tid >> 5, 0) - 8;
    const bool gemm = cta < NGEMM;
    const int bt = cta >> 3, nt = cta & 7;
    const int ncin = cin_count(cta);
    unsigned epoch;
    auto load_cw = [&]() {
      if (elect1()) {
        asm volatile("fence.proxy.async.global;" ::: "memory");
        mbar_expect_tx(bars + 8 * BAR_CW, CW_BYTES);
        bulk_load(sb + OFF_CW, gp.s->cw, CW_CUT * 1792, bars + 8 * BAR_CW);
        bulk_load(sb + OFF_CW2, gp.s->cw + CW_CUT * 1792 / 16, (22 - CW_CUT) * 1792, bars + 8 * BAR_CW);
        bulk_load(sb + OFF_CWL, gp.s->cw + CW_MAIN / 16, CW_LIN, bars + 8 * BAR_CW);
      }
    };
    if (!gemm) {
      epoch = gp.s->epoch[cta] + 1;
#pragma unroll 1
      for (int i = pw * 32 + lane; i < NC_EXTRA * 13; i += 128)
        asm volatile("cp.async.ca.shared.global [%0], [%1], 8;" ::"r"(sb + XOFF_CIDX + i * 8), "l"(idx + cin_row(cta, i / 13) * NF + i % 13 * 2) : "memory");
      if (elect1()) {
#pragma unroll 1
        for (int i = 0; i < NPAIR; i++) mbar_init(sb + XOFF_BAR + (pw * NPAIR + i) * 8, pw & 1 ? 4 : 1);
        asm volatile("fence.mbarrier_init.release.cluster;" ::: "memory");
      }
      asm volatile("cp.async.wait_all;" ::: "memory");
      bar_sync<6, 128>();
      if (elect1()) mbar_arrive(bars + 8 * BAR_GDONE);
      __syncwarp();
      if (pw == 3) {
        flag_wait(&gp.s->foldflag, epoch * NEXTRA * 8, 0);
        __syncwarp();
        load_cw();
      }
      if (elect1()) {
        const int wg = pw & 1;
#pragma unroll 1
        for (int t = pw < 2 ? -1 : 1; t < NPAIR; t += t < 0 ? 1 : 2) {
          const int j = t < 0 ? 0 : 2 * t + 1, n = t < 0 || t == NPAIR - 1 ? 1 : 2;
          const uint32_t cb = t < 0 ? bars + 8 * (BAR_C0 + wg) : sb + XOFF_BAR + (wg * 2 * NPAIR + t) * 8;
          if (t == 0 || t == 1) mbar_wait(ev_bar(bars, EV_END), 0);
          if (t >= 4) mbar_wait(cb + 8 * (NPAIR - 4), 0);
          mbar_expect_tx(cb, n * NF * 128);
#pragma unroll 1
          for (int i = 0; i < n; i++) {
            const uint32_t d = sb + (t < 0 ? OFF_GIDX + wg * XSLOT : XOFF_SLOT + (wg * 8 + (t & 3) * 2 + i) * XSLOT);
            const uint32_t ia = sb + XOFF_CIDX + (wg * (NC_EXTRA / 2) + j + i) * NF * 4;
#pragma unroll 1
            for (int k = 0; k < NF; k += 2) {
              const int2 r = lds64(ia + k * 4);
              tma_row(d + k * 128, &tmT, r.x, cb);
              tma_row(d + (k + 1) * 128, &tmT, r.y, cb);
            }
          }
        }
      }
      __syncwarp();
    } else {
      epoch = lds32(bars + 8 * BAR_EPOCH);
      if (pw == 3) {
        mbar_wait(ev_bar(bars, EV_CW), 0);
        load_cw();
      }
      constexpr int n0 = NC_WG0;
      const uint32_t ep = sb + OFF_EPI + (lane & 3) * 16, pk = sb + (pw * 32 + lane) * 16;
      float r2 = 0.f, r3 = 0.f;
      mbar_wait(bars + 8 * BAR_GDONE, 0);
      mbar_wait(bars + 8 * BAR_X0, 0);
      asm volatile("fence.proxy.async.global;" ::: "memory");
#pragma unroll 1
      for (int k = 0; k < 5; k++) {
        const int n = pw + 4 * k, wg = n > 1 && ((n & 1) || n == 2), j = n == 1 ? 1 : n < 3 ? 0 : n - 1 - wg;
        const int m = min((wg ? ncin - n0 : n0) - j, j ? 2 : 1), r = wg * n0 + j;
        const uint32_t cb = bars + 8 * (j ? BAR_CFULL + wg * 8 + (j >> 1) : BAR_C0 + wg), d = sb + slot_of(wg, j);
        if (n >= 2 && n < 12) {
          const int e = n == 2 ? EV_CW : n < 7 ? EV_SLOT : EV_END;
          mbar_wait(ev_bar(bars, e), 0);
        }
        auto load_sample = [&](int i) {
          const int4 u = lds128(sb + OFF_CIDX + (r + i) * 32), v = lds128(sb + OFF_CIDX + (r + i) * 32 + 16);
          const uint32_t a = d + i * XSLOT;
          tma_row(a, &tmC, (cta * 32 + r + i) * FS, cb);
          tma_row(a + (FS + 0) * 128, &tmT, u.x, cb);
          tma_row(a + (FS + 1) * 128, &tmT, u.y, cb);
          tma_row(a + (FS + 2) * 128, &tmT, u.z, cb);
          tma_row(a + (FS + 3) * 128, &tmT, u.w, cb);
          tma_row(a + (FS + 4) * 128, &tmT, v.x, cb);
          tma_row(a + (FS + 5) * 128, &tmT, v.y, cb);
          tma_row(a + (FS + 6) * 128, &tmT, v.z, cb);
          tma_row(a + (FS + 7) * 128, &tmT, v.w, cb);
        };
        if (m > 0 && elect1()) {
          mbar_expect_tx(cb, m * NF * 128);
#pragma unroll 1
          for (int i = 0; i < m; i++) load_sample(i);
        }
        __syncwarp();
        if (k == 0 || k == 4) continue;
        if (k == 1) {
          mbar_wait(bars + 8 * BAR_PARK, 0);
        }
        uint32_t a = k == 3 ? OFF_PARK2 : OFF_PARK + (k - 1) * 8 * 2048, b = (k - 1) * 8 * 64;
#pragma unroll 1
        for (const uint32_t e = b + 8 * 64; b != e; a += BGN * 2048, b += BGN * 64) {
          float4 v[BGN], q[BGN];
#pragma unroll
          for (int i = 0; i < BGN; i++) { v[i] = lds128f(pk, a + i * 2048); q[i] = lds128f(ep, b + i * 64); }
#pragma unroll
          for (int i = 0; i < BGN; i++) {
            r2 = gelu_acc(v[i].x, q[i].x, q[i].z, r2);
            r3 = gelu_acc(v[i].z, q[i].x, q[i].z, r3);
            r2 = gelu_acc(v[i].y, q[i].y, q[i].w, r2);
            r3 = gelu_acc(v[i].w, q[i].y, q[i].w, r3);
          }
        }
      }
      const float4 w = lds128f(pk + OFF_RS0);
      const int2 v = lds64(sb + OFF_RS1 + (pw * 32 + lane) * 8);
      uint2* dst = gp.s->part + (nt * NB + bt * 256 + pw * 16);
      const uint32_t o = (lane & 1) * 8 + (lane & 2) * 32 + (lane >> 2);
      put_tagged(dst + (o ^ ((cta & 2) * 64 + (~cta & 1) * 64)), quad_sum(w.x, w.y, w.z, w.w, lane), epoch);
      put_tagged(dst + (o ^ ((~cta & 2) * 64)), quad_sum(__int_as_float(v.x), __int_as_float(v.y), r2, r3, lane), epoch);
    }
    if (pw == 3 || !gemm) {
      float s = (sb & 0xFFFFFF) == SMEM_BASE ? bf2f(bout[0]) : __int_as_float(0x7fc00000);
      const int r = gemm ? lane : pw * (NC_EXTRA / 4) + min(lane, NC_EXTRA / 4 - 1), row = cin_row(cta, r);
      const uint2* src = gp.s->part + row;
      uint2 v[8];
#pragma unroll 1
      for (int i = 0; i < 100000; i++) {
        unsigned miss = 0;
#pragma unroll
        for (int n = 0; n < 8; n++)
          asm volatile("ld.relaxed.gpu.global.v2.b32 {%0, %1}, [%2];" : "=r"(v[n].x), "=r"(v[n].y) : "l"(src + n * NB) : "memory");
#pragma unroll
        for (int n = 0; n < 8; n++) miss |= v[n].y ^ epoch;
        if (__all_sync(0xffffffffu, miss == 0)) break;
        __nanosleep(POLL);
      }
#pragma unroll
      for (int n = 0; n < 8; n++) s += __uint_as_float(v[n].x);
      sts64f(sb + OFF_DNN + r * 8, s, __int_as_float(row));
      __syncwarp();
      if (lane == 0) mbar_arrive(bars + 8 * BAR_DNN);
      if (pw == 3 && lane == 0) gp.s->epoch[fresh(cta)] = epoch;
    }
    }
  } else {
    const int wg = warp >> 2;
    const int p = tid & 127;
    if (gemm) {
      asm volatile("barrier.cluster.arrive.relaxed.aligned;" ::: "memory");
#pragma unroll
      for (int i = 0; i < 4; i++) {
        const int r = __shfl_sync(0xffffffffu, myidx, 8 * i + 2 * (lane >> 3));
        const int row = warp * 16 + 4 * i + (lane >> 3);
        cpasync16(sb + row * 128 + (((lane & 7) ^ (row & 7)) << 4), table + (size_t)r * 64 + (lane & 7) * 8);
      }
      asm volatile("barrier.cluster.wait.acquire.aligned;" ::: "memory");
    } else {
      fold_weights(smem, sb, cta - NGEMM, wco, gp);
    }
    asm volatile("setmaxnreg.inc.sync.aligned.u32 224;");
    float r0 = 0.f, r1 = 0.f, r2 = 0.f, r3 = 0.f;
    CinCtx c;
    float accA[28];
    uint32_t xA[10][2], z[8];
    const uint32_t ep = sb + OFF_EPI + (lane & 3) * 16;
    auto load_w = [&](int t) {
      const int w = warp & 3;
      if (w < 3 && elect1())
        tma_load(sb + (b_w(t) + b_ws(t) * w) * UNIT, &tmW, nt * 192 + w * 64, (NF - 1 - t) * 64, full_bar(bars, NF + t));
    };
    auto keep_x = [&](int f, int u) {
      if (warp == 0 && elect1()) tma_store(&tmS, f * 64, cta * 32, sb + (u + rank) * UNIT + (nt >> 2) * 4096);
    };
    auto role = [&](int w) { int c; asm volatile("mov.u32 %0, %%ctaid.x;" : "=r"(c)); return c < NGEMM && wg == w; };
    if (role(0)) {
      bar_sync<1, 128>();
      asm volatile("setmaxnreg.inc.sync.aligned.u32 256;");
      float d0[96], dx[32], dw[96];
      Gelu<24> g0;
      mbar_wait(bars + 8 * BAR_W0, 0);
      asm volatile("cp.async.wait_all;" ::: "memory");
      asm volatile("fence.proxy.async.shared::cta;" ::: "memory");
      bar_sync<2, 256>();
      const uint64_t dA0 = desc_x(rank), dA1 = desc_x(rank ^ 1);
      wg_fence();
#pragma unroll
      for (int k = 0; k < 4; k++) {
        wgmma_ss_n256(dw, dx, dA0 + 2 * k, desc_w(U_W) + 128 * k, k != 0);
        wgmma_ss_n192(d0, dA1 + 2 * k, desc_w(U_W) + 128 * k, k != 0);
      }
      wg_commit();
      keep_x(0, 0);
#pragma unroll 1
      for (int f = 1; f < NF - 3; f++) {
        mbar_wait(full_bar(bars, f), 0);
        const int st = (STAGES >> (2 * f)) & 3, xo = (st == 3 ? U_SP : 2 * st) * (UNIT / 16);
        const uint64_t dB = desc_w(U_W + 4 * st);
        wg_fence();
        wgmma_ss_n256(dw, dx, dA0 + xo, dB, 1);
        wgmma_ss_n192(d0, dA1 + xo, dB, 1);
        wg_commit();
        store_read<0>();
        wg_wait<1>();
        if (p < (f > FS ? 4 : 2)) mbar_arrive_cta(ev_bar(bars, f - 1), p & 1);
#pragma unroll
        for (int k = 1; k < 4; k++) {
          wgmma_ss_n256(dw, dx, dA0 + xo + 2 * k, dB + 128 * k, 1);
          wgmma_ss_n192(d0, dA1 + xo + 2 * k, dB + 128 * k, 1);
        }
        wg_commit();
        if (f < FS) keep_x(f, 2 * st);
      }
      {
        constexpr int x3 = 2 * (UNIT / 16), x4 = U_SP * (UNIT / 16), x5 = 4 * (UNIT / 16);
        const uint64_t dB3 = desc_w(U_W + 4), dB4 = desc_w(U_W + 12), dB5 = desc_w(U_W + 8);
        mbar_wait(full_bar(bars, NF - 3), 0);
        tile_step(d0, dA1 + x3, dB3);
        wg_wait<1>();
        if (p < 4) mbar_arrive_cta(ev_bar(bars, NF - 4), p & 1);
        mbar_wait(full_bar(bars, NF - 2), 0);
        tile_step(d0, dA1 + x4, dB4);
        mbar_wait(full_bar(bars, NF - 1), 0);
        tile_step(d0, dA1 + x5, dB5);
        wide_step(dw, dx, dA0 + x3, dB3);
        g0.start(ep);
        wg_wait<1>();
        wide_step(dw, dx, dA0 + x4, dB4);
        g0.part<0, PE1>(d0, r0, r1, bars + 8 * BAR_W0);
        pin(r0, r1, ep, gp.zero);
        wg_wait<1>();
        if (p < 4) mbar_arrive_cta(ev_bar(bars, NF - 3), p & 1);
        wide_step<0, HK>(dw, dx, dA0 + x5, dB5);
        g0.part<PE1, PE2>(d0, r0, r1, bars + 8 * BAR_W0);
        pin(r0, r1, ep, gp.zero);
        wg_wait<1>();
        bar_arrive<4, 256>();
        if (p < 4) mbar_arrive_cta(ev_bar(bars, NF - 2), p & 1);
        wide_step<HK, 4>(dw, dx, dA0 + x5, dB5);
        g0.part<PE2, PE0>(d0, r0, r1);
        pin(r0, r1, ep, gp.zero);
        wg_wait<0>();
        load_w(3);
        if (p < 4) mbar_arrive_cta(ev_bar(bars, NF - 1), p & 1);
        asm volatile("cp.async.bulk.wait_group 0;" ::: "memory");
        if (warp == 0 && elect1()) mbar_arrive(bars + 8 * BAR_X0);
      }
      g0.part<PE0, 24>(d0, r0, r1);
      Gelu<8> gx;
      gx.start(ep + 24 * 64);
      gx.part<0, 8>(dx, r2, r3);
      float d1[96];
      hand_on(d1, dw);
      asm volatile("setmaxnreg.dec.sync.aligned.u32 224;");
      Gelu<24> g1;
      g1.start(ep);
      g1.part<0, 24>(d1, r2, r3);
    }
    if (role(1)) {
      float d0[96], dw[96];
      asm volatile("cp.async.wait_all;" ::: "memory");
      asm volatile("fence.proxy.async.shared::cta;" ::: "memory");
      bar_arrive<2, 256>();
      {
        const int col = p < 96 ? nt * 96 + p : 768 + (nt >> 2) * 32 + (p - 96);
        const uint32_t bb = __ldg(reinterpret_cast<const uint32_t*>(b1) + col), ww = __ldg(reinterpret_cast<const uint32_t*>(w2) + col);
        reinterpret_cast<float4*>(smem + OFF_EPI)[p] =
            make_float4(ALPHA * bf_lo(bb), ALPHA * bf_hi(bb), (0.5f / ALPHA) * bf_lo(ww), (0.5f / ALPHA) * bf_hi(ww));
      }
      mbar_wait(bars + 8 * BAR_W0, 0);
      mbar_wait(bars + 8 * BAR_FULL, 0);
      wg_fence();
#pragma unroll
      for (int k = 0; k < 4; k++) {
        wgmma_ss_n192(d0, desc_x(U_XB) + 2 * k, desc_w(U_W) + 128 * k, k != 0);
        wgmma_ss_n192(dw, desc_x(U_XB + 1) + 2 * k, desc_w(U_W) + 128 * k, k != 0);
      }
      wg_commit();
      int s = 1;
#pragma unroll 1
      for (int f = 1; f < FS; f++) {
        mbar_wait(full_bar(bars, f), 0);
        const uint64_t dA = desc_x(U_XB + 2 * s), dB = desc_w(U_W + 4 * s);
        wg_fence();
        wgmma_ss_n192(d0, dA, dB, 1);
        wgmma_ss_n192(dw, dA + 512, dB, 1);
        wg_commit();
        wg_wait<1>();
        if (p < 2) mbar_arrive_cta(ev_bar(bars, f - 1), p);
#pragma unroll
        for (int k = 1; k < 4; k++) {
          wgmma_ss_n192(d0, dA + 2 * k, dB + 128 * k, 1);
          wgmma_ss_n192(dw, dA + 512 + 2 * k, dB + 128 * k, 1);
        }
        wg_commit();
        if (++s == 3) s = 0;
      }
      wg_wait<0>();
      if (p < 2) mbar_arrive_cta(ev_bar(bars, FS - 1), p);
      {
        const uint32_t a = sb + OFF_GIDX + 64 * NF * 4;
        int v[4];
#pragma unroll
        for (int i = 0; i < 4; i++) v[i] = lds32(a + (((p & 15) * 4 + i) * NF + (NF - 1 - (p >> 4))) * 4);
        const int2 w = lds64(sb + OFF_GIDX + (((nt >> 2) * 32 + (p >> 2)) * NF + FS + (p & 3) * 2) * 4);
        asm volatile("st.shared.v2.b32 [%0], {%1, %2};" ::"r"(sb + OFF_CIDX + p * 8), "r"(w.x), "r"(w.y) : "memory");
        bar_sync<3, 128>();
        asm volatile("st.shared.v4.b32 [%0], {%1, %2, %3, %4};" ::"r"(sb + OFF_TIDX + p * 16), "r"(v[0]), "r"(v[1]), "r"(v[2]), "r"(v[3]) : "memory");
        bar_sync<3, 128>();
        if (p < 2) {
          const unsigned epoch = gp.s->epoch[cta] + 1;
          flag_wait(&gp.s->foldflag, epoch * NEXTRA * 8, 0);
          sts32f(bars + 8 * BAR_EPOCH, __uint_as_float(epoch));
          mbar_arrive(bars + 8 * BAR_T);
        }
        __syncwarp();
      }
      mbar_wait(full_bar(bars, NF), 0);
      bar_sync<4, 256>();
#pragma unroll
      for (int t = 0; t < 4; t++) {
        if (t) mbar_wait(full_bar(bars, NF + t), 0);
        const uint64_t dA = desc_x(b_x(t)), dB = desc_w(b_w(t), b_ws(t));
        wg_fence();
#pragma unroll
        for (int k = 0; k < 4; k++) {
          wgmma_ss_n192(d0, dA + 2 * k, dB + 128 * k, 1);
          wgmma_ss_n192(dw, dA + 512 + 2 * k, dB + 128 * k, 1);
          if (k == 1 && t) {
            wg_commit();
            wg_wait<1>();
            wg_fence();
          }
        }
        wg_commit();
        if (t) {
          if (t == 1) mbar_wait(ev_bar(bars, NF - 1), 0);
          load_w(3 + t);
          if (t == 1 && p < 4) mbar_arrive_cta(ev_bar(bars, 26), p & 1);
        }
      }
      mbar_wait(full_bar(bars, NF + 4), 0);
      tile_step(d0, desc_x(b_x(4)), desc_w(b_w(4)));
      wg_wait<1>();
      load_w(7);
      if (p < 4) mbar_arrive(ev_bar(bars, EV_CW));
      mbar_wait(full_bar(bars, NF + 5), 0);
      tile_step(d0, desc_x(b_x(5)), desc_w(b_w(5)));
      mbar_wait(full_bar(bars, NF + 6), 0);
      tile_step(d0, desc_x(b_x(6)), desc_w(b_w(6)));
      mbar_wait(full_bar(bars, NF + 7), 0);
      tile_step(d0, desc_x(b_x(7)), desc_w(b_w(7), 4));
      tile_step(dw, desc_x(b_x(4) + 1), desc_w(b_w(4)));
      Gelu<24> g0;
      g0.start(ep);
      wg_wait<1>();
      tile_step(dw, desc_x(b_x(5) + 1), desc_w(b_w(5)));
      g0.part<0, PS>(d0, r0, r1);
      pin(r0, r1, ep, gp.zero);
      wg_wait<1>();
      if (p < 4) mbar_arrive(ev_bar(bars, EV_SLOT));
      tile_step(dw, desc_x(b_x(6) + 1), desc_w(b_w(6)));
      g0.part<PS, PS + PS2>(d0, r0, r1);
      pin(r0, r1, ep, gp.zero);
      wg_wait<1>();
      tile_step(dw, desc_x(b_x(7) + 1), desc_w(b_w(7), 4));
      g0.part<PS + PS2, 24>(d0, r0, r1);
      sts64f(sb + OFF_RS1 + p * 8, r0, r1);
      cin_begin(c, sb, 1, slot_of(1, 0), xA, accA, z);
      if (p < 4) mbar_arrive(ev_bar(bars, EV_END));
#pragma unroll
      for (int i = 0; i < 24; i++)
        sts128f(sb + p * 16 + (i < 16 ? OFF_PARK + i * 2048 : OFF_PARK2 + (i - 16) * 2048), dw[4 * i], dw[4 * i + 1], dw[4 * i + 2], dw[4 * i + 3]);
      __syncwarp();
      if (lane == 0) mbar_arrive(bars + 8 * BAR_PARK);
    }
    if (!role(1)) {
      cin_begin(c, sb, wg, OFF_GIDX + wg * XSLOT, xA, accA, z);
      sts128f(sb + OFF_RS0 + p * 16, r0, r1, r2, r3);
      __syncwarp();
      if (lane == 0) mbar_arrive(bars + 8 * BAR_PARK);
    }

    {
    int cta, tid;
    asm volatile("mov.u32 %0, %%ctaid.x;" : "=r"(cta));
    asm volatile("mov.u32 %0, %%tid.x;" : "=r"(tid));
    cta = __shfl_sync(0xffffffffu, cta, 0);
    const bool gemm = cta < NGEMM;
    const int p = tid & 127, wg = __shfl_sync(0xffffffffu, tid >> 7, 0);
    const int ncin = cin_count(cta);
    const int n0 = gemm ? NC_WG0 : NC_EXTRA / 2;
    const int rb = wg ? n0 : 0;
    const int nj = wg ? ncin - n0 : n0;
    cin_setup(c, sb, wg, p, gemm, nj, gp.zero);
    uint32_t fa = sb + (gemm ? slot_of(wg, (p >> 3) + 1) + NF * 128 : (wg ? XOFF_CIN1 : XOFF_CIN0) + (p >> 3) * CROW) + (p & 7) * 16, fd = sb + OFF_DNN + rb * 8;
    asm volatile("" : "+r"(fa), "+r"(fd));
    auto wg_sync = [&]() { if (wg == 0) bar_sync<1, 128>(); else bar_sync<3, 128>(); };
    mbar_wait(gemm ? bars + 8 * BAR_GDONE : ev_bar(bars, EV_END), 0);
    cin_run(c, nj, xA, accA, z, [&]() {
      mbar_wait(bars + 8 * BAR_DNN, 0);
    }, [&](int j) {
    });
    int2 dn = lds64(fd + (p >> 3) * 8);
    __nv_bfloat16* op = out + dn.y;
    float d = (p & 7) == 0 ? __int_as_float(dn.x) : 0.f;
    asm volatile("" : "+f"(d), "+l"(op));
    wg_sync();
#pragma unroll 1
    for (int r = 0;;) {
      const float4 v0 = lds128f(fa), v1 = lds128f(fa + 128), v2 = lds128f(fa + 256), v3 = lds128f(fa + 384);
      float s = (((v0.x + v0.y) + (v0.z + v0.w)) + ((v1.x + v1.y) + (v1.z + v1.w))) +
                (((v2.x + v2.y) + (v2.z + v2.w)) + (((v3.x + v3.y) + d) + (v3.z + v3.w)));
      s += __shfl_xor_sync(0xffffffffu, s, 1);
      s += __shfl_xor_sync(0xffffffffu, s, 2);
      s += __shfl_xor_sync(0xffffffffu, s, 4);
      if ((p & 7) == 0 && r + (p >> 3) < nj) *op = __float2bfloat16(s);
      r += 16;
      if (r >= nj) break;
      fa += 16 * CROW;
      dn = lds64(fd + (r + (p >> 3)) * 8);
      op = out + dn.y;
      d = (p & 7) == 0 ? __int_as_float(dn.x) : 0.f;
    }
    }
  }
}

typedef CUresult (*EncodeFn)(CUtensorMap*, CUtensorMapDataType, cuuint32_t, void*, const cuuint64_t*, const cuuint64_t*,
                             const cuuint32_t*, const cuuint32_t*, CUtensorMapInterleave, CUtensorMapSwizzle,
                             CUtensorMapL2promotion, CUtensorMapFloatOOBfill);

extern "C" void kernel_launch(void* const* d_in, const int* in_sizes, int n_in, void* d_out, int out_size) {
  void* fn = nullptr;
  cudaDriverEntryPointQueryResult q;
  cudaGetDriverEntryPoint("cuTensorMapEncodeTiled", &fn, cudaEnableDefault, &q);
  EncodeFn enc = (EncodeFn)fn;
  CUtensorMap tmW, tmT, tmS, tmC;
  const cuuint32_t es[3] = {1, 1, 1};
  {
    cuuint64_t dims[2] = {DIN, DIN}, st[1] = {DIN * 2};
    cuuint32_t box[2] = {64, 64};
    enc(&tmW, CU_TENSOR_MAP_DATA_TYPE_BFLOAT16, 2, d_in[4], dims, st, box, es, CU_TENSOR_MAP_INTERLEAVE_NONE,
        CU_TENSOR_MAP_SWIZZLE_128B, CU_TENSOR_MAP_L2_PROMOTION_NONE, CU_TENSOR_MAP_FLOAT_OOB_FILL_NONE);
  }
  {
    cuuint64_t dims[2] = {64, (cuuint64_t)(in_sizes[1] / 64)}, st[1] = {128};
    cuuint32_t box[2] = {64, 1};
    enc(&tmT, CU_TENSOR_MAP_DATA_TYPE_BFLOAT16, 2, d_in[1], dims, st, box, es, CU_TENSOR_MAP_INTERLEAVE_NONE,
        CU_TENSOR_MAP_SWIZZLE_128B, CU_TENSOR_MAP_L2_PROMOTION_NONE, CU_TENSOR_MAP_FLOAT_OOB_FILL_NONE);
  }
  void* x0 = nullptr;
  cudaGetSymbolAddress(&x0, g_x0);
  {
    cuuint64_t dims[2] = {FS * 64, NB}, st[1] = {FS * 128};
    cuuint32_t box[2] = {64, NC_GEMM + 1};
    enc(&tmS, CU_TENSOR_MAP_DATA_TYPE_BFLOAT16, 2, x0, dims, st, box, es, CU_TENSOR_MAP_INTERLEAVE_NONE,
        CU_TENSOR_MAP_SWIZZLE_128B, CU_TENSOR_MAP_L2_PROMOTION_NONE, CU_TENSOR_MAP_FLOAT_OOB_FILL_NONE);
  }
  {
    cuuint64_t dims[2] = {64, NB * FS}, st[1] = {128};
    cuuint32_t box[2] = {64, FS};
    enc(&tmC, CU_TENSOR_MAP_DATA_TYPE_BFLOAT16, 2, x0, dims, st, box, es, CU_TENSOR_MAP_INTERLEAVE_NONE,
        CU_TENSOR_MAP_SWIZZLE_128B, CU_TENSOR_MAP_L2_PROMOTION_NONE, CU_TENSOR_MAP_FLOAT_OOB_FILL_NONE);
  }
  GPtr gp;
  gp.zero = 0;
  cudaGetSymbolAddress((void**)&gp.s, g_scratch);
  cudaGetSymbolAddress((void**)&gp.tab, g_slot_tab);
  cudaFuncSetAttribute(xdeepfm_kernel, cudaFuncAttributeMaxDynamicSharedMemorySize, SMEM_BYTES);
  xdeepfm_kernel<<<GRID, 384, SMEM_BYTES, cudaStreamPerThread>>>(
      (const int*)d_in[0], (const __nv_bfloat16*)d_in[1], (const __nv_bfloat16*)d_in[4], (const __nv_bfloat16*)d_in[5],
      (const __nv_bfloat16*)d_in[6], (const __nv_bfloat16*)d_in[2], (const __nv_bfloat16*)d_in[3],
      (const __nv_bfloat16*)d_in[7], (__nv_bfloat16*)d_out, gp, tmW, tmT, tmS, tmC);
}
```

```cpp
#include <cuda_runtime.h>
#include <cuda_bf16.h>
#include <cuda.h>
#include <stdint.h>

__device__ __forceinline__ void wgmma_ss_n256(float (&d)[96], float (&e)[32], uint64_t descA, uint64_t descB, int scaleD) {
  asm volatile("{\n.reg .pred p;\nsetp.ne.b32 p, %130, 0;\n"
      "wgmma.mma_async.sync.aligned.m64n256k16.f32.bf16.bf16 {"
      "%0, %1, %2, %3, %4, %5, %6, %7, %8, %9, %10, %11, %12, %13, %14, %15,"
      "%16, %17, %18, %19, %20, %21, %22, %23, %24, %25, %26, %27, %28, %29, %30, %31,"
      "%32, %33, %34, %35, %36, %37, %38, %39, %40, %41, %42, %43, %44, %45, %46, %47,"
      "%48, %49, %50, %51, %52, %53, %54, %55, %56, %57, %58, %59, %60, %61, %62, %63,"
      "%64, %65, %66, %67, %68, %69, %70, %71, %72, %73, %74, %75, %76, %77, %78, %79,"
      "%80, %81, %82, %83, %84, %85, %86, %87, %88, %89, %90, %91, %92, %93, %94, %95,"
      "%96, %97, %98, %99, %100, %101, %102, %103, %104, %105, %106, %107, %108, %109, %110, %111,"
      "%112, %113, %114, %115, %116, %117, %118, %119, %120, %121, %122, %123, %124, %125, %126, %127"
      "}, %128, %129, p, 1, 1, 0, 1;\n}\n"
      : "+f"(d[0]), "+f"(d[1]), "+f"(d[2]), "+f"(d[3]), "+f"(d[4]), "+f"(d[5]), "+f"(d[6]), "+f"(d[7]),
        "+f"(d[8]), "+f"(d[9]), "+f"(d[10]), "+f"(d[11]), "+f"(d[12]), "+f"(d[13]), "+f"(d[14]), "+f"(d[15]),
        "+f"(d[16]), "+f"(d[17]), "+f"(d[18]), "+f"(d[19]), "+f"(d[20]), "+f"(d[21]), "+f"(d[22]), "+f"(d[23]),
        "+f"(d[24]), "+f"(d[25]), "+f"(d[26]), "+f"(d[27]), "+f"(d[28]), "+f"(d[29]), "+f"(d[30]), "+f"(d[31]),
        "+f"(d[32]), "+f"(d[33]), "+f"(d[34]), "+f"(d[35]), "+f"(d[36]), "+f"(d[37]), "+f"(d[38]), "+f"(d[39]),
        "+f"(d[40]), "+f"(d[41]), "+f"(d[42]), "+f"(d[43]), "+f"(d[44]), "+f"(d[45]), "+f"(d[46]), "+f"(d[47]),
        "+f"(d[48]), "+f"(d[49]), "+f"(d[50]), "+f"(d[51]), "+f"(d[52]), "+f"(d[53]), "+f"(d[54]), "+f"(d[55]),
        "+f"(d[56]), "+f"(d[57]), "+f"(d[58]), "+f"(d[59]), "+f"(d[60]), "+f"(d[61]), "+f"(d[62]), "+f"(d[63]),
        "+f"(d[64]), "+f"(d[65]), "+f"(d[66]), "+f"(d[67]), "+f"(d[68]), "+f"(d[69]), "+f"(d[70]), "+f"(d[71]),
        "+f"(d[72]), "+f"(d[73]), "+f"(d[74]), "+f"(d[75]), "+f"(d[76]), "+f"(d[77]), "+f"(d[78]), "+f"(d[79]),
        "+f"(d[80]), "+f"(d[81]), "+f"(d[82]), "+f"(d[83]), "+f"(d[84]), "+f"(d[85]), "+f"(d[86]), "+f"(d[87]),
        "+f"(d[88]), "+f"(d[89]), "+f"(d[90]), "+f"(d[91]), "+f"(d[92]), "+f"(d[93]), "+f"(d[94]), "+f"(d[95]),
        "+f"(e[0]), "+f"(e[1]), "+f"(e[2]), "+f"(e[3]), "+f"(e[4]), "+f"(e[5]), "+f"(e[6]), "+f"(e[7]),
        "+f"(e[8]), "+f"(e[9]), "+f"(e[10]), "+f"(e[11]), "+f"(e[12]), "+f"(e[13]), "+f"(e[14]), "+f"(e[15]),
        "+f"(e[16]), "+f"(e[17]), "+f"(e[18]), "+f"(e[19]), "+f"(e[20]), "+f"(e[21]), "+f"(e[22]), "+f"(e[23]),
        "+f"(e[24]), "+f"(e[25]), "+f"(e[26]), "+f"(e[27]), "+f"(e[28]), "+f"(e[29]), "+f"(e[30]), "+f"(e[31])
      : "l"(descA), "l"(descB), "r"(scaleD));
}
__device__ __forceinline__ void wgmma_ss_n192(float (&d)[96], uint64_t descA, uint64_t descB, int scaleD) {
  asm volatile("{\n.reg .pred p;\nsetp.ne.b32 p, %98, 0;\n"
      "wgmma.mma_async.sync.aligned.m64n192k16.f32.bf16.bf16 {"
      "%0, %1, %2, %3, %4, %5, %6, %7, %8, %9, %10, %11, %12, %13, %14, %15,"
      "%16, %17, %18, %19, %20, %21, %22, %23, %24, %25, %26, %27, %28, %29, %30, %31,"
      "%32, %33, %34, %35, %36, %37, %38, %39, %40, %41, %42, %43, %44, %45, %46, %47,"
      "%48, %49, %50, %51, %52, %53, %54, %55, %56, %57, %58, %59, %60, %61, %62, %63,"
      "%64, %65, %66, %67, %68, %69, %70, %71, %72, %73, %74, %75, %76, %77, %78, %79,"
      "%80, %81, %82, %83, %84, %85, %86, %87, %88, %89, %90, %91, %92, %93, %94, %95"
      "}, %96, %97, p, 1, 1, 0, 1;\n}\n"
      : "+f"(d[0]), "+f"(d[1]), "+f"(d[2]), "+f"(d[3]), "+f"(d[4]), "+f"(d[5]), "+f"(d[6]), "+f"(d[7]),
        "+f"(d[8]), "+f"(d[9]), "+f"(d[10]), "+f"(d[11]), "+f"(d[12]), "+f"(d[13]), "+f"(d[14]), "+f"(d[15]),
        "+f"(d[16]), "+f"(d[17]), "+f"(d[18]), "+f"(d[19]), "+f"(d[20]), "+f"(d[21]), "+f"(d[22]), "+f"(d[23]),
        "+f"(d[24]), "+f"(d[25]), "+f"(d[26]), "+f"(d[27]), "+f"(d[28]), "+f"(d[29]), "+f"(d[30]), "+f"(d[31]),
        "+f"(d[32]), "+f"(d[33]), "+f"(d[34]), "+f"(d[35]), "+f"(d[36]), "+f"(d[37]), "+f"(d[38]), "+f"(d[39]),
        "+f"(d[40]), "+f"(d[41]), "+f"(d[42]), "+f"(d[43]), "+f"(d[44]), "+f"(d[45]), "+f"(d[46]), "+f"(d[47]),
        "+f"(d[48]), "+f"(d[49]), "+f"(d[50]), "+f"(d[51]), "+f"(d[52]), "+f"(d[53]), "+f"(d[54]), "+f"(d[55]),
        "+f"(d[56]), "+f"(d[57]), "+f"(d[58]), "+f"(d[59]), "+f"(d[60]), "+f"(d[61]), "+f"(d[62]), "+f"(d[63]),
        "+f"(d[64]), "+f"(d[65]), "+f"(d[66]), "+f"(d[67]), "+f"(d[68]), "+f"(d[69]), "+f"(d[70]), "+f"(d[71]),
        "+f"(d[72]), "+f"(d[73]), "+f"(d[74]), "+f"(d[75]), "+f"(d[76]), "+f"(d[77]), "+f"(d[78]), "+f"(d[79]),
        "+f"(d[80]), "+f"(d[81]), "+f"(d[82]), "+f"(d[83]), "+f"(d[84]), "+f"(d[85]), "+f"(d[86]), "+f"(d[87]),
        "+f"(d[88]), "+f"(d[89]), "+f"(d[90]), "+f"(d[91]), "+f"(d[92]), "+f"(d[93]), "+f"(d[94]), "+f"(d[95])
      : "l"(descA), "l"(descB), "r"(scaleD));
}
template <unsigned long long DESC, int SCALE>
__device__ __forceinline__ void wgmma_rs_n56(float (&d)[28], uint32_t a0, uint32_t a1, uint32_t a2, uint32_t a3) {
  asm volatile("{\n.reg .b64 desc;\nmov.b64 desc, %32;\n"
      "wgmma.mma_async.sync.aligned.m64n56k16.f32.bf16.bf16 {"
      "%0, %1, %2, %3, %4, %5, %6, %7, %8, %9, %10, %11, %12, %13, %14, %15,"
      "%16, %17, %18, %19, %20, %21, %22, %23, %24, %25, %26, %27"
      "}, {%28, %29, %30, %31}, desc, %33, 1, 1, 0;\n}\n"
      : "+f"(d[0]), "+f"(d[1]), "+f"(d[2]), "+f"(d[3]), "+f"(d[4]), "+f"(d[5]), "+f"(d[6]), "+f"(d[7]),
        "+f"(d[8]), "+f"(d[9]), "+f"(d[10]), "+f"(d[11]), "+f"(d[12]), "+f"(d[13]), "+f"(d[14]), "+f"(d[15]),
        "+f"(d[16]), "+f"(d[17]), "+f"(d[18]), "+f"(d[19]), "+f"(d[20]), "+f"(d[21]), "+f"(d[22]), "+f"(d[23]),
        "+f"(d[24]), "+f"(d[25]), "+f"(d[26]), "+f"(d[27])
      : "r"(a0), "r"(a1), "r"(a2), "r"(a3), "n"(DESC), "n"(SCALE));
}
template <unsigned long long DESC, int SCALE>
__device__ __forceinline__ void wgmma_rs_n32(float (&d)[28], uint32_t a0, uint32_t a1, uint32_t a2, uint32_t a3) {
  asm volatile("{\n.reg .b64 desc;\nmov.b64 desc, %20;\n"
      "wgmma.mma_async.sync.aligned.m64n32k16.f32.bf16.bf16 {"
      "%0, %1, %2, %3, %4, %5, %6, %7, %8, %9, %10, %11, %12, %13, %14, %15"
      "}, {%16, %17, %18, %19}, desc, %21, 1, 1, 0;\n}\n"
      : "+f"(d[0]), "+f"(d[1]), "+f"(d[2]), "+f"(d[3]), "+f"(d[4]), "+f"(d[5]), "+f"(d[6]), "+f"(d[7]),
        "+f"(d[8]), "+f"(d[9]), "+f"(d[10]), "+f"(d[11]), "+f"(d[12]), "+f"(d[13]), "+f"(d[14]), "+f"(d[15])
      : "r"(a0), "r"(a1), "r"(a2), "r"(a3), "n"(DESC), "n"(SCALE));
}

constexpr int NB = 4096, NF = 26, DIN = 1664;
constexpr int NGEMM = 128, NEXTRA = 4, GRID = NGEMM + NEXTRA;
constexpr int NC_EXTRA = 76;
constexpr int NC_WG0 = 16;
constexpr int HK = 4;
constexpr int PE0 = 9;
constexpr int WD = 2;
constexpr int GI = 3;
constexpr int PE1 = 4;
constexpr int PE2 = 8;
constexpr int PS2 = 5;
constexpr int POLL = 400;
constexpr int XD = 1000;
constexpr int PX = 2;
constexpr int RC = 168;
constexpr int PREG = 40;
constexpr int PS = 7;
constexpr int RB = 4;
constexpr int NC_GEMM = 29, NBIG = NB - NGEMM * NC_GEMM - NEXTRA * NC_EXTRA;
static_assert(NBIG >= 0 && NBIG <= NGEMM && NC_EXTRA % 4 == 0 && NC_EXTRA <= 96, "split");
constexpr int CW_MAIN = 22 * 1792, CW_LIN = 2 * 1024, CW_BYTES = CW_MAIN + CW_LIN;
constexpr int XSLOT = 4096;

constexpr int UNIT = 8192, FS = 18;
constexpr int U_W = 6, U_XB = 18, U_SP = 24;
constexpr int CW_CUT = 9;
constexpr int OFF_CW = 0, OFF_CW2 = 6 * UNIT, OFF_CWL = 9 * UNIT;
constexpr int CROW = 528;
constexpr int OFF_RS0 = OFF_CWL + CW_LIN;
constexpr int OFF_GIDX = 26 * UNIT;
constexpr int OFF_TIDX = OFF_GIDX + 128 * NF * 4 - 8 * 64 * 4;
constexpr int OFF_CIDX = OFF_GIDX + 128 * NF * 4;
constexpr int OFF_EPI = OFF_CIDX + 32 * 8 * 4;
constexpr int OFF_DNN = OFF_EPI + 128 * 16;
constexpr int OFF_BAR = OFF_DNN + 112 * 8;
constexpr int SMEM_BYTES = OFF_BAR + 92 * 8;
static_assert(CW_CUT * 1792 <= 2 * UNIT && (22 - CW_CUT) * 1792 <= 3 * UNIT , "smem");
constexpr uint32_t SMEM_BASE = 1024;
static_assert(SMEM_BYTES <= 232448, "smem");
static_assert(OFF_EPI % 16 == 0 && OFF_BAR % 8 == 0, "align");
constexpr int XOFF_W3 = 0, XOFF_W2 = 35152, XOFF_W1 = 70304, XOFF_M = XOFF_W1 + 8 * 1352, XOFF_S = XOFF_M + 32 * 40 * 4,
              XOFF_SLOT = 10 * UNIT, XOFF_CIN0 = 2 * UNIT, XOFF_CIN1 = 18 * UNIT, XOFF_CIDX = 22 * UNIT,
              XOFF_BAR = 24 * UNIT, NPAIR = NC_EXTRA / 4;
static_assert(XOFF_S + 14 * 3136 <= 21 * UNIT && 48 * CROW <= 4 * UNIT, "smem");

constexpr int BAR_RS0 = 0,
              BAR_CW = 1,
              BAR_GIDX = 2,
              BAR_X0 = 3,
              BAR_W0 = 4,
              BAR_DNN = 5,
              BAR_T = 6,
              BAR_GDONE = 7,
              BAR_EPOCH = 8,
              BAR_C0 = 9,
              BAR_CFULL = 11,
              BAR_FULL = 27,
              BAR_EV = 61;
constexpr int EV_CW = 27, EV_SLOT = 28, EV_END = 29;
__device__ __forceinline__ uint32_t ev_bar(uint32_t bars, int e) { return bars + 8 * (BAR_EV + e); }
__device__ __forceinline__ uint32_t full_bar(uint32_t bars, int j) { return bars + 8 * (BAR_FULL + j); }
constexpr unsigned long long STAGES = 0xb4b4924924924ull;
__host__ __device__ constexpr int b_x(int t) { return ((0xb2c1430bu >> (4 * t)) & 15) * 2; }
__host__ __device__ constexpr int b_w(int t) { return (0x0d0a120eu >> (8 * (t & 3))) & 31; }
__host__ __device__ constexpr int b_ws(int t) { return (t & 3) == 3 ? 4 : 1; }

struct Scratch {
  uint4 cw[CW_BYTES / 16];
  uint2 part[8 * NB];
  unsigned epoch[GRID];
  unsigned foldflag;
};
__device__ __align__(128) Scratch g_scratch;
__device__ __align__(1024) __nv_bfloat16 g_x0[NB * FS * 64];
struct GPtr { Scratch* s; const uint4* tab; uint32_t zero; };

__device__ __forceinline__ void wg_fence() { asm volatile("wgmma.fence.sync.aligned;" ::: "memory"); }
__device__ __forceinline__ void wg_commit() { asm volatile("wgmma.commit_group.sync.aligned;" ::: "memory"); }
template <int N> __device__ __forceinline__ void wg_wait() { asm volatile("wgmma.wait_group.sync.aligned %0;" ::"n"(N) : "memory"); }
__device__ __forceinline__ uint64_t mkdesc(uint32_t addr, uint32_t lbo, uint32_t sbo, uint32_t swz) {
  return (uint64_t)((addr & 0x3FFFF) >> 4) | ((uint64_t)(lbo >> 4) << 16) | ((uint64_t)(sbo >> 4) << 32) | ((uint64_t)swz << 62);
}
__device__ __forceinline__ bool elect1() {
  uint32_t p; asm volatile("{\n.reg .pred p;\nelect.sync _|p, 0xffffffff;\nselp.b32 %0, 1, 0, p;\n}" : "=r"(p)); return p;
}
__device__ __forceinline__ int fresh(int v) { asm volatile("" : "+r"(v)); return v; }
__device__ __forceinline__ void mbar_init(uint32_t bar, uint32_t cnt) { asm volatile("mbarrier.init.shared::cta.b64 [%0], %1;" ::"r"(bar), "r"(cnt) : "memory"); }
__device__ __forceinline__ void mbar_arrive(uint32_t bar) { asm volatile("mbarrier.arrive.shared::cta.b64 _, [%0];" ::"r"(bar) : "memory"); }
__device__ __forceinline__ void mbar_arrive_cta(uint32_t bar, uint32_t cta) {
  asm volatile("{\n.reg .b32 r;\nmapa.shared::cluster.u32 r, %0, %1;\nmbarrier.arrive.shared::cluster.b64 _, [r];\n}" ::"r"(bar), "r"(cta) : "memory");
}
__device__ __forceinline__ void mbar_expect_tx(uint32_t bar, uint32_t bytes) { asm volatile("mbarrier.arrive.expect_tx.shared::cta.b64 _, [%0], %1;" ::"r"(bar), "r"(bytes) : "memory"); }
__device__ __forceinline__ void mbar_wait(uint32_t bar, uint32_t parity) {
  asm volatile("{\n.reg .pred p;\nLAB_WAIT:\n"
               "mbarrier.try_wait.parity.shared::cta.b64 p, [%0], %1;\n"
               "@!p bra LAB_WAIT;\n}" ::"r"(bar), "r"(parity) : "memory");
}
__device__ __forceinline__ void flag_wait(const unsigned* p, unsigned target, unsigned sleep_ns) {
  asm volatile("{\n.reg .pred p;\n.reg .u32 n, v;\nmov.u32 n, 0;\nLAB_WAIT:\n"
               "ld.acquire.gpu.global.u32 v, [%0];\n"
               "sub.u32 v, v, %1;\n"
               "setp.ge.s32 p, v, 0;\n"
               "@p bra DONE;\n"
               "nanosleep.u32 %2;\n"
               "add.u32 n, n, 1;\n"
               "setp.lt.u32 p, n, 400000;\n"
               "@p bra LAB_WAIT;\n"
               "DONE:\n}" ::"l"(p), "r"(target), "r"(sleep_ns) : "memory");
}
__device__ __forceinline__ void put_tagged(uint2* p, float v, unsigned tag) {
  asm volatile("st.relaxed.gpu.global.v2.b32 [%0], {%1, %2};" ::"l"(p), "r"(__float_as_uint(v)), "r"(tag) : "memory");
}
__device__ __forceinline__ void flag_add(unsigned* p) { asm volatile("red.release.gpu.global.add.u32 [%0], 1;" ::"l"(p) : "memory"); }
__device__ __forceinline__ void tma_load(uint32_t dst, const CUtensorMap* tm, int c0, int c1, uint32_t bar) {
  asm volatile("cp.async.bulk.tensor.2d.shared::cluster.global.mbarrier::complete_tx::bytes [%0], [%1, {%3, %4}], [%2];"
               ::"r"(dst), "l"(tm), "r"(bar), "r"(c0), "r"(c1) : "memory");
}
__device__ __forceinline__ void tma_row_mc(uint32_t dst, const CUtensorMap* tm, int row, uint32_t bar) {
  asm volatile("cp.async.bulk.tensor.2d.shared::cluster.global.mbarrier::complete_tx::bytes.multicast::cluster [%0], [%1, {%3, %4}], [%2], %5;"
               ::"r"(dst), "l"(tm), "r"(bar), "r"(0), "r"(row), "h"((uint16_t)3));
}
__device__ __forceinline__ void tma_row(uint32_t dst, const CUtensorMap* tm, int row, uint32_t bar) {
  asm volatile("cp.async.bulk.tensor.2d.shared::cluster.global.mbarrier::complete_tx::bytes [%0], [%1, {%3, %4}], [%2];"
               ::"r"(dst), "l"(tm), "r"(bar), "r"(0), "r"(row));
}
__device__ __forceinline__ void tma_store(const CUtensorMap* tm, int c0, int c1, uint32_t src) {
  asm volatile("cp.async.bulk.tensor.2d.global.shared::cta.bulk_group [%0, {%1, %2}], [%3];\ncp.async.bulk.commit_group;"
               ::"l"(tm), "r"(c0), "r"(c1), "r"(src) : "memory");
}
template <int N> __device__ __forceinline__ void store_read() { asm volatile("cp.async.bulk.wait_group.read %0;" ::"n"(N) : "memory"); }
__device__ __forceinline__ void bulk_load(uint32_t dst, const void* src, uint32_t bytes, uint32_t bar) {
  asm volatile("cp.async.bulk.shared::cluster.global.mbarrier::complete_tx::bytes [%0], [%1], %2, [%3];"
               ::"r"(dst), "l"(src), "r"(bytes), "r"(bar));
}
__device__ __forceinline__ void l2_prefetch(const void* src, uint32_t bytes) {
  asm volatile("cp.async.bulk.prefetch.L2.global [%0], %1;" ::"l"(src), "r"(bytes));
}
__device__ __forceinline__ void w_prefetch(const __nv_bfloat16* w1, int f, int cta, int piece) {
  l2_prefetch(w1 + (f * 64 + (cta >> 3) * 4 + (cta & 1) * 2 + (piece & 1)) * DIN + (piece < 2 ? (cta & 6) * 192 : 1536 + (cta & 4) * 16),
              piece < 2 ? 768 : 128);
}
__device__ __forceinline__ void cpasync16(uint32_t dst, const void* src) {
  asm volatile("cp.async.cg.shared.global [%0], [%1], 16;" ::"r"(dst), "l"(src) : "memory");
}
template <int ID, int N> __device__ __forceinline__ void bar_sync() { asm volatile("bar.sync %0, %1;" ::"n"(ID), "n"(N) : "memory"); }
template <int ID, int N> __device__ __forceinline__ void bar_arrive() { asm volatile("bar.arrive %0, %1;" ::"n"(ID), "n"(N) : "memory"); }
__device__ __forceinline__ void ldsm4t(uint32_t& a, uint32_t& b, uint32_t& c, uint32_t& d, uint32_t addr) {
  asm volatile("ldmatrix.sync.aligned.m8n8.x4.trans.shared.b16 {%0,%1,%2,%3}, [%4];" : "=r"(a), "=r"(b), "=r"(c), "=r"(d) : "r"(addr) : "memory");
}
__device__ __forceinline__ int lds32(uint32_t addr) { int v; asm volatile("ld.shared.b32 %0, [%1];" : "=r"(v) : "r"(addr)); return v; }
__device__ __forceinline__ int2 lds64(uint32_t addr) { int2 v; asm volatile("ld.shared.v2.b32 {%0,%1}, [%2];" : "=r"(v.x), "=r"(v.y) : "r"(addr)); return v; }
__device__ __forceinline__ int4 lds128(uint32_t addr) {
  int4 v; asm volatile("ld.shared.v4.b32 {%0,%1,%2,%3}, [%4];" : "=r"(v.x), "=r"(v.y), "=r"(v.z), "=r"(v.w) : "r"(addr)); return v;
}
__device__ __forceinline__ float4 lds128f(uint32_t addr) {
  float4 v; asm volatile("ld.shared.v4.f32 {%0,%1,%2,%3}, [%4];" : "=f"(v.x), "=f"(v.y), "=f"(v.z), "=f"(v.w) : "r"(addr) : "memory"); return v;
}
__device__ __forceinline__ float4 lds128f(uint32_t addr, uint32_t off) {
  float4 v;
  asm volatile("{\n.reg .u32 t;\nadd.u32 t, %4, %5;\nld.shared.v4.f32 {%0,%1,%2,%3}, [t];\n}" : "=f"(v.x), "=f"(v.y), "=f"(v.z), "=f"(v.w) : "r"(addr), "r"(off) : "memory");
  return v;
}
__device__ __forceinline__ void sts32f(uint32_t addr, float v) { asm volatile("st.shared.f32 [%0], %1;" ::"r"(addr), "f"(v) : "memory"); }
__device__ __forceinline__ float bf_lo(uint32_t v) { return __uint_as_float(v << 16); }
__device__ __forceinline__ float bf_hi(uint32_t v) { return __uint_as_float(v & 0xffff0000u); }
__device__ __forceinline__ float bf2f(__nv_bfloat16 v) { return __bfloat162float(v); }

__device__ __forceinline__ uint32_t mul2(uint32_t a, uint32_t b) {
  uint32_t r; asm volatile("mul.rn.bf16x2 %0, %1, %2;" : "=r"(r) : "r"(a), "r"(b)); return r;
}
__device__ __forceinline__ uint32_t mul2lo(uint32_t a, uint32_t b) {
  uint32_t r;
  asm volatile("{\n.reg .b16 l, h;\n.reg .b32 t;\nmov.b32 {l, h}, %2;\nmov.b32 t, {l, l};\nmul.rn.bf16x2 %0, %1, t;\n}" : "=r"(r) : "r"(a), "r"(b));
  return r;
}
__device__ __forceinline__ uint32_t mul2hi(uint32_t a, uint32_t b) {
  uint32_t r;
  asm volatile("{\n.reg .b16 l, h;\n.reg .b32 t;\nmov.b32 {l, h}, %2;\nmov.b32 t, {h, h};\nmul.rn.bf16x2 %0, %1, t;\n}" : "=r"(r) : "r"(a), "r"(b));
  return r;
}

__host__ __device__ constexpr int xfield(int r, int e, int c) {
  return r == 9 ? 24 + e : 8 * (r / 3) + 2 * (((r % 3) + c) & 3) + (((r % 3) == 2 && c >= 2) ? 1 - e : e);
}
__host__ __device__ constexpr int blk_a(int b) { return b < 12 ? 3 * (b / 8) + ((b & 3) == 3) : (b < 15 ? 3 * (b - 12) : 3 * (b - 15)); }
__host__ __device__ constexpr int blk_b(int b) { return b < 12 ? 3 * (b < 4 ? 1 : 2) + ((b & 3) == 3 ? 0 : (b & 3)) : (b < 15 ? 3 * (b - 12) + 1 : 9); }
__host__ __device__ constexpr int slot_pq(int u, int e, int c) {
  return u < 36 ? (xfield(blk_a(u >> 1), e, c) | (xfield(blk_b(u >> 1), u & 1, c) << 8))
       : u < 39 ? (xfield(3 * (u - 36), e, c) * 257)
       : u < 42 ? (xfield(3 * (u - 39), e, c) | (xfield(3 * (u - 39) + 2, e, c) << 8))
       : u == 42 ? (xfield(3 * e, 0, c) | (xfield(3 * e, 1, c) << 8))
       : u == 43 ? (e == 0 ? (xfield(6, 0, c) | (xfield(6, 1, c) << 8))
                           : (c == 0 ? 24 * 257 : c == 1 ? 25 * 257 : c == 2 ? (24 | 25 << 8) : 26 * 257))
       : u < 47 ? (xfield(3 * (u - 44), e, c) | (26 << 8))
       : (c == 0 ? ((24 + e) | 26 << 8) : 27 * 257);
}
struct SlotTab { uint32_t v[48 * 8]; };
constexpr SlotTab make_slot_tab() {
  SlotTab t{};
  for (int u = 0; u < 48; u++)
    for (int k = 0; k < 8; k++) {
      const int pq = slot_pq(u, k & 1, k >> 1), p = pq & 255, q = pq >> 8;
      t.v[u * 8 + k] = (uint32_t)((p * 28 + q) * 4) | ((uint32_t)(((p != q && q < 26) ? q * 28 + p : 27 * 28 + 27) * 4) << 16);
    }
  return t;
}
__device__ __align__(16) const SlotTab g_slot_tab = make_slot_tab();

struct CinCtx {
  uint32_t o03, o14, o25, o69, o78, cin, selA, selB;
  bool ones, lead;
  uint32_t so, so2, co, co2, bar, jump, dslot, last;
  bool ring;
};
constexpr unsigned long long CW_DESC = (unsigned long long)((SMEM_BASE + OFF_CW) >> 4) | (8ull << 16) | (16ull << 32);
constexpr unsigned long long CWL_DESC = CW_DESC + (OFF_CWL - OFF_CW) / 16;

template <int U>
__device__ __forceinline__ uint32_t zreg(const uint32_t (&x)[10][2], int h, const CinCtx& c) {
  if constexpr (U < 36) {
    if constexpr (U & 1) return mul2hi(x[blk_a(U >> 1)][h], x[blk_b(U >> 1)][h]);
    else return mul2lo(x[blk_a(U >> 1)][h], x[blk_b(U >> 1)][h]);
  } else if constexpr (U < 39) {
    return mul2(x[3 * (U - 36)][h], x[3 * (U - 36)][h]);
  } else if constexpr (U < 42) {
    return mul2(x[3 * (U - 39)][h], x[3 * (U - 39) + 2][h]);
  } else if constexpr (U == 42) {
    return mul2(__byte_perm(x[0][h], x[3][h], 0x5410), __byte_perm(x[0][h], x[3][h], 0x7632));
  } else {
    const uint32_t f = c.ones ? 0x3f803f80u : x[9][h];
    return mul2(__byte_perm(x[6][h], f, c.selA), __byte_perm(x[6][h], f, c.selB));
  }
}

template <int G>
__device__ __forceinline__ void z_fill(uint32_t (&z)[8], const uint32_t (&x)[10][2], const CinCtx& c) {
  z[0] = zreg<4 * G>(x, 0, c);     z[1] = zreg<4 * G>(x, 1, c);
  z[2] = zreg<4 * G + 1>(x, 0, c); z[3] = zreg<4 * G + 1>(x, 1, c);
  z[4] = zreg<4 * G + 2>(x, 0, c); z[5] = zreg<4 * G + 2>(x, 1, c);
  z[6] = zreg<4 * G + 3>(x, 0, c); z[7] = zreg<4 * G + 3>(x, 1, c);
}
__host__ __device__ constexpr unsigned long long cw_desc(int s) { return CW_DESC + (s < CW_CUT ? s * 1792 : OFF_CW2 - OFF_CW + (s - CW_CUT) * 1792) / 16; }
template <int G>
__device__ __forceinline__ void z_mma(float (&acc)[28], const uint32_t (&z)[8]) {
  wgmma_rs_n56<cw_desc(2 * G), G != 0>(acc, z[0], z[1], z[2], z[3]);
  wgmma_rs_n56<cw_desc(2 * G + 1), 1>(acc, z[4], z[5], z[6], z[7]);
}

__device__ __forceinline__ void cin_finish(const CinCtx& c, float (&acc)[28], uint32_t out) {
#pragma unroll
  for (int i = 0; i < 28; i++) asm volatile("" : "+f"(acc[i]));
  float s0 = acc[12] * acc[13], s1 = acc[14] * acc[15];
#pragma unroll
  for (int i = 0; i < 12; i += 2) {
    s0 = fmaf(acc[i], acc[16 + i], s0);
    s1 = fmaf(acc[i + 1], acc[17 + i], s1);
  }
  sts32f(c.cin + out, s0 + s1);
}

__device__ __forceinline__ void cin_ldsm(const CinCtx& c, uint32_t so, uint32_t (&x)[10][2]) {
  ldsm4t(x[0][0], x[0][1], x[3][0], x[3][1], so + c.o03);
  ldsm4t(x[1][0], x[1][1], x[4][0], x[4][1], so + c.o14);
  ldsm4t(x[2][0], x[2][1], x[5][0], x[5][1], so + c.o25);
  ldsm4t(x[6][0], x[6][1], x[9][0], x[9][1], so + c.o69);
  ldsm4t(x[7][0], x[7][1], x[8][0], x[8][1], so + c.o78);
}
__device__ __forceinline__ void cin_load(const CinCtx& c, int k, bool real, uint32_t (&x)[10][2]) {
  if (k == 0 && real) mbar_wait(c.bar, 0);
  cin_ldsm(c, k ? c.so2 : c.so, x);
  if (k == 1 && c.lead) mbar_arrive(c.bar + 8 * NPAIR);
}
__device__ __forceinline__ void cin_advance(CinCtx& c) {
  const uint32_t d = c.so == c.jump ? c.dslot : 2 * XSLOT;
  c.so += d; c.so2 += d;
  c.co = c.ring ? c.co + 2 * CROW : c.so;
  c.bar += 8;
}
constexpr int CG_WAIT = 2;
constexpr int CG_FIN = 2;
constexpr int CG_HEAD = 3;
constexpr int CG_LIN = 5;
constexpr int CG_LOAD = 6;
constexpr int CG_N = 11;
static_assert(CG_FIN >= CG_WAIT && CG_FIN < CG_HEAD && CG_LOAD >= CG_HEAD && CG_LIN >= CG_HEAD && CG_LOAD < 10, "CIN schedule");
template <int G, int GEND, typename F>
__device__ __forceinline__ void cin_groups(const CinCtx& c, const uint32_t (&x)[10][2], float (&acc)[28], uint32_t (&z)[8],
                                           int q, bool more, uint32_t (&xn)[10][2], F finish) {
  if constexpr (G < GEND) {
    wg_fence();
    if constexpr (G == CG_LIN) {
      wgmma_rs_n32<CWL_DESC, 1>(acc, x[0][0], x[0][1], x[3][0], x[3][1]);
      wgmma_rs_n32<CWL_DESC + 1024 / 16, 1>(acc, x[6][0], x[6][1], x[9][0], x[9][1]);
    }
    z_mma<G>(acc, z);
    wg_commit();
    if constexpr (G == CG_LOAD) cin_load(c, q, more, xn);
    uint32_t zn[8];
    if constexpr (G + 1 < CG_N) z_fill<G + 1>(zn, x, c); else z_fill<0>(zn, xn, c);
    if constexpr (G == CG_FIN) finish();
    wg_wait<CG_WAIT>();
    if constexpr (G + 1 < GEND) cin_groups<G + 1, GEND>(c, x, acc, zn, q, more, xn, finish);
    else {
#pragma unroll
      for (int i = 0; i < 8; i++) z[i] = zn[i];
    }
    if constexpr (G + 1 < GEND) {
#pragma unroll
      for (int i = 0; i < 8; i++) z[i] = zn[i];
    }
  }
}
template <typename F>
__device__ __forceinline__ void cin_head(const CinCtx& c, uint32_t (&x)[10][2], float (&acc)[28], uint32_t (&z)[8], F finish) {
  cin_groups<0, CG_HEAD>(c, x, acc, z, 0, false, x, finish);
}
__device__ __forceinline__ void cin_tail(const CinCtx& c, const uint32_t (&x)[10][2], float (&acc)[28], uint32_t (&z)[8],
                                         int q, bool more, uint32_t (&xn)[10][2]) {
  cin_groups<CG_HEAD, CG_N>(c, x, acc, z, q, more, xn, []() {});
}

__device__ __forceinline__ int slot_of(int wg, int j) {
  return wg ? (j == 0 ? 9 * UNIT + XSLOT : j <= 8 ? 2 * UNIT + (j - 1) * XSLOT : 21 * UNIT + (j - 9) * XSLOT)
            : (j < 3 ? OFF_GIDX + j * XSLOT : 14 * UNIT + (j - 3) * XSLOT);
}

__device__ __forceinline__ void cin_begin(CinCtx& c, uint32_t sb, int wg, uint32_t first, uint32_t (&x)[10][2], float (&acc)[28], uint32_t (&z)[8]) {
  int t; asm volatile("mov.u32 %0, %%tid.x;" : "=r"(t));
  const int m = t & 16, f0 = t & 7, f1 = (f0 + 2) & 7, f2 = (f0 ^ 4) ^ (f0 >> 2);
  const uint32_t base = sb + m * 64, ch = (t & 96) + (t & 8) * 2;
  c.o03 = (base + f0 * 0x90) ^ ch;
  c.o14 = (base + f1 * 0x90) ^ ch;
  c.o25 = (base + f2 * 0x90) ^ ch;
  c.o69 = (base + 2048 + (m ? f0 & 1 : f0) * 0x90) ^ ch;
  c.o78 = m ? c.o25 + 1024 : c.o14 + 2048;
  mbar_wait(sb + OFF_BAR + 8 * BAR_GDONE, 0);
  mbar_wait(sb + OFF_BAR + 8 * (BAR_C0 + wg), 0);
  cin_ldsm(c, first, x);
  mbar_wait(sb + OFF_BAR + 8 * BAR_CW, 0);
  z_fill<0>(z, x, c);
  cin_head(c, x, acc, z, []() {});
}
__device__ __forceinline__ void cin_setup(CinCtx& c, uint32_t sb, int wg, int p, bool gemm, int nj, uint32_t zero) {
  c.bar = sb + (gemm ? OFF_BAR + 8 * (BAR_CFULL + wg * 8) : XOFF_BAR + wg * 16 * NPAIR);
  c.lead = (p & 31) == 0 && !gemm; c.ring = !gemm;
  c.so = !gemm ? XOFF_SLOT + 8 * wg * XSLOT : wg ? 2 * UNIT : OFF_GIDX + XSLOT;
  c.jump = c.so + (gemm && !wg ? 0 : 6 * XSLOT);
  c.dslot = !gemm ? -6 * XSLOT : wg ? 19 * UNIT - 6 * XSLOT : 14 * UNIT - OFF_GIDX - XSLOT;
  c.co = gemm ? c.so : (wg ? XOFF_CIN1 : XOFF_CIN0) - NF * 128;
  c.co2 = gemm ? XSLOT : CROW;
  c.so2 = c.so + XSLOT + zero;
  c.last = gemm ? slot_of(wg, (nj - 1) | 1) : c.co + ((nj - 1) & ~1) * CROW;
  c.cin = sb + NF * 128 + p * 4;
  const int q = p & 3;
  c.selA = q == 1 ? 0x7610 : 0x5410;
  c.selB = q == 0 ? 0x5432 : 0x7632;
  c.ones = q == 3;
}
template <typename F2, typename F3>
__device__ __forceinline__ void cin_run(CinCtx& c, int nj, uint32_t (&xA)[10][2], float (&accA)[28], uint32_t (&z)[8], F2 before_end, F3 st5) {
  float accB[28];
  uint32_t xB[10][2];
  const uint32_t lastA = nj & 1 ? c.last : 0;
#pragma unroll 1
  for (int j = 0;; j += 2) {
    cin_tail(c, xA, accA, z, 0, c.co != lastA, xB);
    if (c.co == lastA) { before_end(); wg_wait<0>(); cin_finish(c, accA, c.co); break; }
    cin_head(c, xB, accB, z, [&]() { st5(j); cin_finish(c, accA, c.co); });
    cin_tail(c, xB, accB, z, 1, true, xA);
    if (c.co == c.last) { before_end(); wg_wait<0>(); cin_finish(c, accB, c.co + c.co2); break; }
    cin_head(c, xA, accA, z, [&]() { st5(j + 1); cin_finish(c, accB, c.co + c.co2); });
    cin_advance(c);
  }
}

constexpr float ALPHA = 0.3292034911525734f, KAPPA = 2.423681954311584f;
__device__ __forceinline__ float gelu_acc(float v, float ab, float w, float s, float alpha = ALPHA) {
  const float a = fmaf(v, alpha, ab);
  const float u = a * fmaf(a, a, KAPPA);
  float th; asm("tanh.approx.f32 %0, %1;" : "=f"(th) : "f"(u));
  return fmaf(fmaf(a, th, a), w, s);
}

constexpr int QD = 2;
template <int NG>
struct Gelu {
  float4 q[QD + 1];
  uint32_t ep;
  template <int I0 = 0>
  __device__ __forceinline__ void start(uint32_t a) {
    ep = a;
#pragma unroll
    for (int i = I0; i < I0 + QD; i++) q[i % (QD + 1)] = lds128f(ep + i * 64);
  }
  template <int I0, int I1>
  __device__ __forceinline__ void part(float (&d)[4 * NG], float& r0, float& r1, uint32_t done) {
    float alpha;
    asm volatile("{\n.reg .pred p;\nmbarrier.test_wait.parity.shared::cta.b64 p, [%1], 0;\nselp.f32 %0, %2, 0f7FC00000, p;\n}"
                 : "=f"(alpha) : "r"(done), "f"(ALPHA) : "memory");
    part<I0, I1>(d, r0, r1, alpha);
  }
  template <int I0, int I1>
  __device__ __forceinline__ void part(float (&d)[4 * NG], float& r0, float& r1, float alpha = ALPHA) {
#pragma unroll
    for (int i = I0; i < I1; i++) {
      if (i + QD < NG) q[(i + QD) % (QD + 1)] = lds128f(ep + (i + QD) * 64);
      const float4 v = q[i % (QD + 1)];
#pragma unroll
      for (int e = 0; e < 4; e++) asm volatile("" : "+f"(d[4 * i + e]));
      const float al = i < I0 + QD ? alpha : ALPHA;
      r0 = gelu_acc(d[4 * i + 0], v.x, v.z, r0, al);
      r0 = gelu_acc(d[4 * i + 1], v.y, v.w, r0, al);
      r1 = gelu_acc(d[4 * i + 2], v.x, v.z, r1, al);
      r1 = gelu_acc(d[4 * i + 3], v.y, v.w, r1, al);
    }
    asm volatile("" : "+f"(r0), "+f"(r1));
  }
};
__device__ __forceinline__ float quad_sum(float r0, float r1, float r2, float r3, int lane) {
  const bool b0 = lane & 1, b1 = lane & 2;
  const float a = (b0 ? r1 : r0) + __shfl_xor_sync(0xffffffffu, b0 ? r0 : r1, 1);
  const float b = (b0 ? r3 : r2) + __shfl_xor_sync(0xffffffffu, b0 ? r2 : r3, 1);
  return (b1 ? b : a) + __shfl_xor_sync(0xffffffffu, b1 ? a : b, 2);
}
__device__ __forceinline__ void sts128f(uint32_t addr, float a, float b, float c, float d) {
  asm volatile("st.shared.v4.f32 [%0], {%1, %2, %3, %4};" ::"r"(addr), "f"(a), "f"(b), "f"(c), "f"(d) : "memory");
}
__device__ __forceinline__ void pin(float a, float b, uint32_t addr, uint32_t zero) {
  asm volatile("{\n.reg .pred p;\nsetp.ne.u32 p, %3, 0;\n@p st.shared.v2.f32 [%0], {%1, %2};\n}" ::"r"(addr), "f"(a), "f"(b), "r"(zero) : "memory");
}
template <int I0, int I1>
__device__ __forceinline__ void gelu_slow(float (&d)[96], float& r0, float& r1, uint32_t ep, uint32_t zero) {
#pragma unroll
  for (int i = I0; i < I1; i++) {
    const float4 v = lds128f(ep + i * 64);
#pragma unroll
    for (int e = 0; e < 4; e++) asm volatile("" : "+f"(d[4 * i + e]));
    r0 = gelu_acc(d[4 * i + 0], v.x, v.z, r0);
    r1 = gelu_acc(d[4 * i + 2], v.x, v.z, r1);
    r0 = gelu_acc(d[4 * i + 1], v.y, v.w, r0);
    r1 = gelu_acc(d[4 * i + 3], v.y, v.w, r1);
    pin(r0, r1, zero, zero);
  }
}
__device__ __forceinline__ void hand_on(float (&d)[96], const float (&s)[96]) {
#pragma unroll
  for (int i = 0; i < 96; i++) asm volatile("mov.b32 %0, %1;" : "=f"(d[i]) : "f"(s[i]));
}
__device__ __forceinline__ uint64_t desc_x(int u) { return mkdesc(SMEM_BASE, 16, 1024, 1) + u * (UNIT / 16); }
__device__ __forceinline__ uint64_t desc_w(int u, int stride = 1) { return mkdesc(SMEM_BASE, stride * UNIT, 1024, 1) + u * (UNIT / 16); }
__device__ __forceinline__ void tile_step(float (&d)[96], uint64_t dA, uint64_t dB) {
  wg_fence();
#pragma unroll
  for (int k = 0; k < 4; k++) wgmma_ss_n192(d, dA + 2 * k, dB + 128 * k, 1);
  wg_commit();
}
template <int K0 = 0, int K1 = 4>
__device__ __forceinline__ void wide_step(float (&d)[96], float (&e)[32], uint64_t dA, uint64_t dB) {
  wg_fence();
#pragma unroll
  for (int k = K0; k < K1; k++) wgmma_ss_n256(d, e, dA + 2 * k, dB + 128 * k, 1);
  wg_commit();
}
__device__ __forceinline__ int cin_row(int c, int j) {
  if (c >= NGEMM) {
    const int e = (c - NGEMM) * NC_EXTRA + j;
    c = e < 256 ? e >> 1 : NBIG + e - 256;
    j = e < 256 ? 30 + (e & 1) : 29;
  }
  return (c >> 3) * 256 + (c & 2) * 64 + (c & 1) * 64 + (c & 4) * 8 + j;
}
__device__ __forceinline__ int cin_count(int c) {
  return c < NGEMM ? NC_GEMM + (c < NBIG) : NC_EXTRA;
}

__device__ __forceinline__ void cin_job(uint32_t sb, int cta, int n, const CUtensorMap* tmC, const CUtensorMap* tmT) {
  const int wg = n > 1 && ((n & 1) || n == 2), j = n == 1 ? 1 : n < 3 ? 0 : n - 1 - wg;
  const int m = min((wg ? cin_count(cta) - NC_WG0 : NC_WG0) - j, j ? 2 : 1), r = wg * NC_WG0 + j;
  const uint32_t cb = sb + OFF_BAR + 8 * (j ? BAR_CFULL + wg * 8 + (j >> 1) : BAR_C0 + wg), d = sb + slot_of(wg, j);
  if (m > 0 && elect1()) {
    mbar_expect_tx(cb, m * NF * 128);
#pragma unroll 1
    for (int i = 0; i < m; i++) {
      const int4 u = lds128(sb + OFF_CIDX + (r + i) * 32), v = lds128(sb + OFF_CIDX + (r + i) * 32 + 16);
      const uint32_t a = d + i * XSLOT;
      tma_row(a, tmC, (cta * 32 + r + i) * FS, cb);
      tma_row(a + (FS + 0) * 128, tmT, u.x, cb);
      tma_row(a + (FS + 1) * 128, tmT, u.y, cb);
      tma_row(a + (FS + 2) * 128, tmT, u.z, cb);
      tma_row(a + (FS + 3) * 128, tmT, u.w, cb);
      tma_row(a + (FS + 4) * 128, tmT, v.x, cb);
      tma_row(a + (FS + 5) * 128, tmT, v.y, cb);
      tma_row(a + (FS + 6) * 128, tmT, v.z, cb);
      tma_row(a + (FS + 7) * 128, tmT, v.w, cb);
    }
  }
  __syncwarp();
}
__device__ __forceinline__ void row_job(uint32_t d, uint32_t ia, int n, uint32_t cb, const CUtensorMap* tmT) {
  if (elect1()) {
    mbar_expect_tx(cb, n * NF * 128);
#pragma unroll 1
    for (int i = 0; i < n; i++, d += XSLOT - NF * 128) {
#pragma unroll 1
      for (const uint32_t e = d + NF * 128; d != e; d += 256, ia += 8) {
        const int2 r = lds64(ia);
        tma_row(d, tmT, r.x, cb);
        tma_row(d + 128, tmT, r.y, cb);
      }
    }
  }
  __syncwarp();
}

__device__ __forceinline__ int fold_i0(int e) { return e < 2 ? 7 * e : 2 + 6 * e; }
__device__ __forceinline__ uint32_t ldg16(const void* p) { uint16_t v; asm volatile("ld.global.nc.u16 %0, [%1];" : "=h"(v) : "l"(p)); return v; }
__device__ __forceinline__ uint4 ldg128(const void* p) {
  uint4 v; asm volatile("ld.global.nc.v4.u32 {%0,%1,%2,%3}, [%4];" : "=r"(v.x), "=r"(v.y), "=r"(v.z), "=r"(v.w) : "l"(p)); return v;
}
__device__ __forceinline__ void sts64f(uint32_t addr, float a, float b) { asm volatile("st.shared.v2.f32 [%0], {%1, %2};" ::"r"(addr), "f"(a), "f"(b) : "memory"); }
__device__ __forceinline__ float to_tf32(float v) { uint32_t r; asm("cvt.rna.tf32.f32 %0, %1;" : "=r"(r) : "f"(v)); return __uint_as_float(r); }
__device__ __forceinline__ uint4 fold_chunk(uint32_t base, const uint4 t0, const uint4 t1) {
  const uint32_t t[8] = {t0.x, t0.y, t0.z, t0.w, t1.x, t1.y, t1.z, t1.w};
  uint32_t v[4];
#pragma unroll
  for (int c = 0; c < 4; c++) {
    const float w0 = __int_as_float(lds32(base + (t[2 * c] & 0xffff))) + __int_as_float(lds32(base + (t[2 * c] >> 16)));
    const float w1 = __int_as_float(lds32(base + (t[2 * c + 1] & 0xffff))) + __int_as_float(lds32(base + (t[2 * c + 1] >> 16)));
    __nv_bfloat162 pk = __floats2bfloat162_rn(w0, w1);
    v[c] = *reinterpret_cast<uint32_t*>(&pk);
  }
  return make_uint4(v[0], v[1], v[2], v[3]);
}
__device__ __forceinline__ int cw_chunk(int u, int n) {
  return ((u < 44 ? (u >> 1) * 1792 : CW_MAIN + ((u - 44) >> 1) * 1024) + (n >> 3) * 256 + (u & 1) * 128 + (n & 7) * 16) >> 4;
}
__device__ __forceinline__ void fold_weights(uint8_t* smem, uint32_t sb, int e, const __nv_bfloat16* __restrict__ wco, const GPtr gp) {
  const int tid = threadIdx.x, lane = tid & 31, warp = tid >> 5;
  const uint32_t bars = sb + OFF_BAR;
  const int i0 = fold_i0(e), i = i0 + warp;
  const bool own = i < fold_i0(e + 1);
  const uint32_t wb16 = ldg16(wco + (lane < NF ? 26 + lane : 0)), wc16 = ldg16(wco + (lane < NF ? 52 + lane : 0));
  const uint32_t w116 = ldg16(wco + (own ? i : 0));
  const uint4* tab = gp.tab;
  const uint4 ta0 = ldg128(tab + 2 * lane), ta1 = ldg128(tab + 2 * lane + 1);
  const uint4 tb0 = ldg128(tab + 64 + 2 * (lane & 15)), tb1 = ldg128(tab + 65 + 2 * (lane & 15));
  asm volatile("barrier.cluster.arrive.relaxed.aligned;\nbarrier.cluster.wait.acquire.aligned;" ::: "memory");
  if (warp >= 6) {
#pragma unroll 1
    for (int t = tid - 192; t < 6 * 20; t += 64) sts64f(sb + XOFF_M + 26 * 160 + t * 8, 0.f, 0.f);
    if (warp == 6 && lane < NF) {
      sts64f(sb + XOFF_M + lane * 160 + 104, bf_lo(wb16), 0.f);
      sts64f(sb + XOFF_M + lane * 160 + 112, 0.f, 0.f);
      sts64f(sb + XOFF_M + lane * 160 + 120, 0.f, 0.f);
    }
    if (warp == 7) {
      gp.s->cw[cw_chunk(lane, 28 + e)] = make_uint4(0, 0, 0, 0);
      if (lane < 16) gp.s->cw[cw_chunk(32 + lane, 28 + e)] = make_uint4(0, 0, 0, 0);
    }
  } else {
    mbar_wait(bars + 8 * BAR_GIDX, 0);
    float m0 = 0.f, m1 = 0.f, m2 = 0.f, m3 = 0.f;
    const uint32_t a = sb + XOFF_W3 + (tid < 169 ? tid : 0) * 8;
#pragma unroll 1
    for (int g = 0; g < NF; g++) {
      const int2 v = lds64(a + g * 1352);
      const float w = __shfl_sync(0xffffffffu, bf_lo(wc16), g);
      m0 = fmaf(w, bf_lo(v.x), m0); m1 = fmaf(w, bf_hi(v.x), m1);
      m2 = fmaf(w, bf_lo(v.y), m2); m3 = fmaf(w, bf_hi(v.y), m3);
    }
    if (tid < 169) {
      const int o = tid * 2, o2 = o + 1;
      sts64f(sb + XOFF_M + (o / 13) * 160 + (o % 13) * 8, to_tf32(m0), to_tf32(m1));
      sts64f(sb + XOFF_M + (o2 / 13) * 160 + (o2 % 13) * 8, to_tf32(m2), to_tf32(m3));
    }
  }
  const uint32_t sT = sb + XOFF_S + warp * 2 * 3136, sA = sT + 3136;
  const int g = lane >> 2, c = lane & 3;
  uint32_t af[2][8];
  mbar_wait(bars + 8 * BAR_FULL, 0);
  if (own) {
#pragma unroll
    for (int k = 0; k < 8; k++) {
      const int h = 4 * k + c;
      const uint32_t a = sb + XOFF_W2 + ((h < NF ? h : 0) * 676 + i * 26 + 2 * g) * 2;
      af[0][k] = lds32(a);
      af[1][k] = lds32(a + (g < 5 ? 32 : 0));
    }
#pragma unroll 1
    for (int o = lane; o < 338; o += 32) {
      const uint32_t v = lds32(sb + XOFF_W1 + (i - (i0 & ~1)) * 1352 + o * 4);
      sts64f(sA + (o / 13) * 112 + (o % 13) * 8, bf_lo(v), bf_hi(v));
    }
    if (lane < 28) sts64f(sA + lane * 112 + 104, 0.f, 0.f);
    if (lane < 2) sts64f(sT + (26 + lane) * 112 + 104, lane == 0 ? bf_lo(w116) : 0.f, 0.f);
  }
  bar_sync<4, 256>();
  if (own) {
#pragma unroll 1
    for (int n = 0; n < 4; n++) {
      float d[2][4] = {};
#pragma unroll
      for (int ks = 0; ks < 4; ks++) {
        const uint32_t b0 = lds32(sb + XOFF_M + (8 * ks + c) * 160 + (8 * n + g) * 4);
        const uint32_t b1 = lds32(sb + XOFF_M + (8 * ks + c + 4) * 160 + (8 * n + g) * 4);
#pragma unroll
        for (int m = 0; m < 2; m++)
          asm volatile("mma.sync.aligned.m16n8k8.row.col.f32.tf32.tf32.f32 {%0,%1,%2,%3}, {%4,%5,%6,%7}, {%8,%9}, {%0,%1,%2,%3};"
                       : "+f"(d[m][0]), "+f"(d[m][1]), "+f"(d[m][2]), "+f"(d[m][3])
                       : "r"(af[m][2 * ks] << 16), "r"(af[m][2 * ks] & 0xffff0000u), "r"(af[m][2 * ks + 1] << 16),
                         "r"(af[m][2 * ks + 1] & 0xffff0000u), "r"(b0), "r"(b1));
      }
      if (n < 3 || c < 2) {
        const uint32_t a = sT + 2 * g * 112 + (8 * n + 2 * c) * 4;
        sts64f(a, d[0][0], d[0][1]);
        sts64f(a + 112, d[0][2], d[0][3]);
        if (g < 5) {
          sts64f(a + 16 * 112, d[1][0], d[1][1]);
          sts64f(a + 17 * 112, d[1][2], d[1][3]);
        }
      }
    }
    __syncwarp();
    const int nt = i < 24 ? i : 2 * i - 24, na = i < 24 ? 32 + i : 2 * i - 23;
#pragma unroll 1
    for (int k = 0; k < 3; k++) {
      const bool isa = k == 1 || (k == 2 && lane >= 16);
      const uint4 v = fold_chunk(isa ? sA : sT, k < 2 ? ta0 : tb0, k < 2 ? ta1 : tb1);
      if (k < 2 || lane < 28 || na < 32) gp.s->cw[cw_chunk(k < 2 ? lane : 32 + (lane & 15), isa ? na : nt)] = v;
    }
  }
  __syncwarp();
  if (lane == 0) flag_add(&gp.s->foldflag);
  bar_sync<4, 256>();
  mbar_wait(bars + 8 * BAR_GDONE, 0);
  if (tid >= 128 && tid < 132) mbar_arrive(ev_bar(bars, EV_END));
}

__global__ void __cluster_dims__(2, 1, 1) __launch_bounds__(384, 1)
xdeepfm_kernel(const int* __restrict__ idx, const __nv_bfloat16* __restrict__ table, const __nv_bfloat16* __restrict__ w1,
               const __nv_bfloat16* __restrict__ b1, const __nv_bfloat16* __restrict__ w2,
               const __nv_bfloat16* __restrict__ ws, const __nv_bfloat16* __restrict__ wco,
               const __nv_bfloat16* __restrict__ bout, __nv_bfloat16* __restrict__ out, const GPtr gp,
               const __grid_constant__ CUtensorMap tmW, const __grid_constant__ CUtensorMap tmT,
               const __grid_constant__ CUtensorMap tmS, const __grid_constant__ CUtensorMap tmC) {
  int myidx, idx1, idx2 = 0, idx3 = 0;
  {
    const int t = threadIdx.x, b = blockIdx.x, half = (b >> 1) ^ (t >= 256 ? t >> 4 : 0);
    const int* ip = idx + (((b >> 3) & 15) * 256 + (half & 1) * 128 + (t < 256 ? t >> 1 : (b & 1) * 64 + ((t >> 1) & 48) + (t & 15))) * NF;
    asm volatile("{\n.reg .pred p;\nsetp.ge.u32 p, %5, 256;\nld.global.nc.v2.s32 {%0, %1}, [%4];\n@p ld.global.nc.v2.s32 {%2, %3}, [%4 + 8];\n}"
                 : "=r"(myidx), "=r"(idx1), "+r"(idx2), "+r"(idx3) : "l"(ip), "r"(t));
  }
  extern __shared__ __align__(1024) uint8_t smem[];
  const uint32_t sb = (uint32_t)__cvta_generic_to_shared(smem);
  const uint32_t bars = sb + OFF_BAR;
  const int tid = threadIdx.x, lane = tid & 31;
  const int warp = __shfl_sync(0xffffffffu, tid >> 5, 0);
  const int cta = blockIdx.x;
  const bool gemm = cta < NGEMM;
  const int nt = cta & 7, rank = cta & 1;

  if (!gemm && warp == 8) __nanosleep(XD);
  if (warp == 8 && elect1()) {
    mbar_init(bars + 8 * BAR_GIDX, 1);
    mbar_init(bars + 8 * BAR_FULL, 1);
    mbar_init(bars + 8 * BAR_W0, 1);
    asm volatile("fence.mbarrier_init.release.cluster;" ::: "memory");
    if (gemm) {
      mbar_expect_tx(bars + 8 * BAR_W0, 4 * UNIT);
#pragma unroll
      for (int i = 0; i < 4; i++)
        tma_load(sb + (U_W + i) * UNIT, &tmW, i < 3 ? nt * 192 + i * 64 : 1536 + (nt >> 2) * 64, 0, bars + 8 * BAR_W0);
      mbar_expect_tx(bars + 8 * BAR_FULL, 2 * UNIT);
    } else {
      const int i0 = fold_i0(cta - NGEMM) & ~1, ni = NF - i0 < 8 ? NF - i0 : 8;
      mbar_expect_tx(bars + 8 * BAR_GIDX, 35152);
      bulk_load(sb + XOFF_W3, ws + 2 * 17576, 35152, bars + 8 * BAR_GIDX);
      mbar_expect_tx(bars + 8 * BAR_FULL, 35152 + ni * 1352);
      bulk_load(sb + XOFF_W1, ws + i0 * 676, ni * 1352, bars + 8 * BAR_FULL);
      bulk_load(sb + XOFF_W2, ws + 17576, 35152, bars + 8 * BAR_FULL);
    }
  }
  if (warp < 8 && elect1()) {
#pragma unroll
    for (int i = 0; i < 8; i++) mbar_init(full_bar(bars, 1 + warp * 8 + i), BAR_FULL + 1 + warp * 8 + i < BAR_EV ? 1 : 4);
    asm volatile("fence.mbarrier_init.release.cluster;" ::: "memory");
  }
  if (warp == 7 && lane >= 16 && (lane & 7) < 7) {
    const int l = lane & 7;
    asm volatile("prefetch.global.L2 [%0];" ::"l"(w1 + (((cta >> 3 & 15) * 2 + (cta & 1)) * 2 + ((lane >> 3) & 1)) * DIN + (l < 6 ? (cta & 6) * 192 + l * 64 : 1536 + (cta & 4) * 16)));
  }

  if (warp >= 8) {
    const int pw = warp - 8;
    if (pw && elect1()) {
      if (pw == 1) {
        asm volatile("prefetch.tensormap [%0];" ::"l"(&tmT) : "memory");
        mbar_init(bars + 8 * BAR_CW, 1);
        mbar_init(bars + 8 * BAR_X0, 1);
        mbar_init(bars + 8 * BAR_T, 2);
        mbar_init(bars + 8 * BAR_RS0, 4);
        mbar_init(bars + 8 * BAR_GDONE, 4);
        mbar_init(bars + 8 * BAR_DNN, gemm ? 1 : 4);
      } else {
#pragma unroll
        for (int i = 0; i < 9; i++) mbar_init(bars + 8 * (BAR_C0 + (pw - 2) * 9 + i), 1);
      }
      asm volatile("fence.mbarrier_init.release.cluster;" ::: "memory");
    }
    __syncwarp();
    asm volatile("barrier.cluster.arrive.relaxed.aligned;" ::: "memory");
    asm volatile("barrier.cluster.wait.acquire.aligned;" ::: "memory");
    asm volatile("setmaxnreg.dec.sync.aligned.u32 24;");
    if (gemm) {
      {
        const uint32_t a = sb + OFF_GIDX + ((lane >> 4) * 64 + pw * 16 + (lane & 15)) * NF * 4;
        asm volatile("st.shared.v2.b32 [%0], {%1, %2};\nst.shared.v2.b32 [%0 + 8], {%3, %4};"
                     ::"r"(a), "r"(myidx), "r"(idx1), "r"(idx2), "r"(idx3) : "memory");
        __syncwarp();
      }
      if (elect1()) {
#pragma unroll 1
        for (int j = 0; j < 16; j += 8) {
          int r[8];
#pragma unroll
          for (int i = 0; i < 8; i++) r[i] = lds32(sb + OFF_GIDX + ((64 + pw * 16 + j + i) * NF) * 4);
#pragma unroll
          for (int i = 0; i < 8; i++) tma_row_mc(sb + U_XB * UNIT + (rank * 64 + pw * 16 + j + i) * 128, &tmT, r[i], bars + 8 * BAR_FULL);
        }
        if (pw == 0) asm volatile("prefetch.tensormap [%0];" ::"l"(&tmS) : "memory");
        int s = 1;
#pragma unroll 1
        for (int fi = 1; fi < NF; fi++) {
          const int f = fresh(fi), pw = fresh(warp) - 8, ct = fresh(cta), nt = ct & 7;
          const int t = f - FS, st = t < 0 ? s : (t & 3) ^ ((t >> 1) & 1), e = f - 3 - (t > 1);
          const uint32_t fb = full_bar(bars, f), ia = sb + OFF_GIDX + (pw * 16 * NF + f) * 4;
          const uint32_t d = sb + (st == 3 ? U_SP : 2 * st) * UNIT + ((ct & 1) * 64 + pw * 16) * 128;
          if (f == 4) mbar_wait(bars + 8 * BAR_GIDX, 0);
          int r[2][RB];
#pragma unroll
          for (int i = 0; i < RB; i++) r[0][i] = lds32(ia + i * NF * 4);
          if (e >= 0) mbar_wait(ev_bar(bars, e), 0);
          if (pw == 0) mbar_expect_tx(fb, t < 0 ? 8 * UNIT : 6 * UNIT);
#pragma unroll
          for (int j = 0; j < 16 / RB; j++) {
#pragma unroll
            for (int i = 0; i < RB; i++) r[(j + 1) & 1][i] = lds32(ia + (RB * j + RB + i + (RB * j + RB >= 16) * 48) * NF * 4);
#pragma unroll
            for (int i = 0; i < RB; i++) tma_row_mc(d + (RB * j + i) * 128, &tmT, r[j & 1][i], fb);
          }
          if (t < 0) {
#pragma unroll
            for (int j = 0; j < 16 / RB; j++) {
              if (j + 1 < 16 / RB) {
#pragma unroll
                for (int i = 0; i < RB; i++) r[(j + 1) & 1][i] = lds32(ia + (64 + RB * j + RB + i) * NF * 4);
              }
#pragma unroll
              for (int i = 0; i < RB; i++) tma_row_mc(d + U_XB * UNIT + (RB * j + i) * 128, &tmT, r[j & 1][i], fb);
            }
          }
          tma_load(sb + (U_W + 4 * st + pw) * UNIT, &tmW, pw < 3 ? nt * 192 + pw * 64 : 1536 + (nt >> 2) * 64, f * 64, fb);
          if (f == GI && pw < 2) {
            if (pw == 0) mbar_expect_tx(bars + 8 * BAR_GIDX, 128 * NF * 4);
            bulk_load(sb + OFF_GIDX + pw * 64 * NF * 4, idx + ((ct >> 3) * 256 + (((ct >> 1) ^ pw) & 1) * 128 + (ct & 1) * 64) * NF, 64 * NF * 4, bars + 8 * BAR_GIDX);
          }
          if (f == GI && pw == 2) asm volatile("prefetch.tensormap [%0];" ::"l"(&tmC) : "memory");
          if (f + WD < NF) w_prefetch(w1, f + WD, ct, pw);
          if (++s == 3) s = 0;
        }
        mbar_wait(bars + 8 * BAR_T, 0);
#pragma unroll 1
        for (int ti = 0; ti < 8; ti++) {
          const int t = fresh(ti), pw = fresh(warp) - 8, e = t < 4 ? 22 - !t : 19 + t;
          const uint32_t ia = sb + OFF_TIDX + t * 256 + pw * 64, fb = full_bar(bars, NF + t);
          const uint32_t d = sb + b_x(t) * UNIT + ((fresh(cta) & 1) * 64 + pw * 16) * 128;
          int4 r[2];
          r[0] = lds128(ia);
          r[1] = lds128(ia + 16);
          mbar_wait(ev_bar(bars, e), 0);
          if (pw == 0) mbar_expect_tx(fb, t < 3 ? 2 * UNIT : 5 * UNIT);
#pragma unroll
          for (int j = 0; j < 4; j++) {
            tma_row_mc(d + (4 * j + 0) * 128, &tmT, r[j & 1].x, fb);
            tma_row_mc(d + (4 * j + 1) * 128, &tmT, r[j & 1].y, fb);
            tma_row_mc(d + (4 * j + 2) * 128, &tmT, r[j & 1].z, fb);
            tma_row_mc(d + (4 * j + 3) * 128, &tmT, r[j & 1].w, fb);
            if (j < 2) r[j & 1] = lds128(ia + 32 + 16 * j);
          }
        }
        mbar_arrive(bars + 8 * BAR_GDONE);
      }
      __syncwarp();
    }
    bar_sync<6, 128>();
    asm volatile("setmaxnreg.inc.sync.aligned.u32 %0;" ::"n"(PREG));
    {
    int cta; asm volatile("mov.u32 %0, %%ctaid.x;" : "=r"(cta));
    int tid; asm volatile("mov.u32 %0, %%tid.x;" : "=r"(tid));
    const int lane = tid & 31, pw = __shfl_sync(0xffffffffu, tid >> 5, 0) - 8;
    const bool gemm = cta < NGEMM;
    auto load_cw = [&]() {
      if (elect1()) {
        asm volatile("fence.proxy.async.global;" ::: "memory");
        mbar_expect_tx(bars + 8 * BAR_CW, CW_BYTES);
        bulk_load(sb + OFF_CW, gp.s->cw, CW_CUT * 1792, bars + 8 * BAR_CW);
        bulk_load(sb + OFF_CW2, gp.s->cw + CW_CUT * 1792 / 16, (22 - CW_CUT) * 1792, bars + 8 * BAR_CW);
        bulk_load(sb + OFF_CWL, gp.s->cw + CW_MAIN / 16, CW_LIN, bars + 8 * BAR_CW);
      }
    };
    if (!gemm) {
      const unsigned epoch = gp.s->epoch[cta] + 1;
      if (tid == 256) sts32f(bars + 8 * BAR_EPOCH, __uint_as_float(epoch));
#pragma unroll 1
      for (int i = pw * 32 + lane; i < NC_EXTRA * 13; i += 128)
        asm volatile("cp.async.ca.shared.global [%0], [%1], 8;" ::"r"(sb + XOFF_CIDX + i * 8), "l"(idx + cin_row(cta, i / 13) * NF + i % 13 * 2) : "memory");
      if (elect1()) {
#pragma unroll 1
        for (int i = 0; i < NPAIR; i++) mbar_init(sb + XOFF_BAR + (pw * NPAIR + i) * 8, pw & 1 ? 4 : 1);
        asm volatile("fence.mbarrier_init.release.cluster;" ::: "memory");
      }
      asm volatile("cp.async.wait_all;" ::: "memory");
      bar_sync<6, 128>();
      if (elect1()) mbar_arrive(bars + 8 * BAR_GDONE);
      __syncwarp();
      if (pw < 2) row_job(sb + OFF_GIDX + pw * XSLOT, sb + XOFF_CIDX + pw * (NC_EXTRA / 2) * NF * 4, 1, bars + 8 * (BAR_C0 + pw), &tmT);
      if (pw == 3) {
        flag_wait(&gp.s->foldflag, epoch * NEXTRA * 8, 0);
        __syncwarp();
        load_cw();
      }
    } else {
      if (pw == 3) {
        mbar_wait(ev_bar(bars, EV_CW), 0);
        load_cw();
      }
      mbar_wait(bars + 8 * BAR_GDONE, 0);
      mbar_wait(bars + 8 * BAR_X0, 0);
      asm volatile("fence.proxy.async.global;" ::: "memory");
#pragma unroll 1
      for (int n = pw; n < 7; n += 4) {
        if (n >= 2) mbar_wait(ev_bar(bars, n == 2 ? EV_CW : EV_SLOT), 0);
        cin_job(sb, cta, n, &tmC, &tmT);
      }
    }
    }
    bar_sync<6, 128>();
    asm volatile("setmaxnreg.inc.sync.aligned.u32 %0;" ::"n"(RC));
  } else {
    const int wg = warp >> 2;
    const int p = tid & 127;
    if (gemm) {
      asm volatile("barrier.cluster.arrive.relaxed.aligned;" ::: "memory");
#pragma unroll
      for (int i = 0; i < 4; i++) {
        const int r = __shfl_sync(0xffffffffu, myidx, 8 * i + 2 * (lane >> 3));
        const int row = warp * 16 + 4 * i + (lane >> 3);
        cpasync16(sb + row * 128 + (((lane & 7) ^ (row & 7)) << 4), table + (size_t)r * 64 + (lane & 7) * 8);
      }
      asm volatile("barrier.cluster.wait.acquire.aligned;" ::: "memory");
    } else {
      fold_weights(smem, sb, cta - NGEMM, wco, gp);
    }
    const uint32_t ep = sb + OFF_EPI + (lane & 3) * 16;
    auto load_w = [&](int t) {
      const int w = warp & 3;
      if (w < 3 && elect1())
        tma_load(sb + (b_w(t) + b_ws(t) * w) * UNIT, &tmW, nt * 192 + w * 64, (NF - 1 - t) * 64, full_bar(bars, NF + t));
    };
    auto keep_x = [&](int f, int u) {
      if (warp == 0 && elect1()) tma_store(&tmS, f * 64, cta * 32, sb + (u + rank) * UNIT + (nt >> 2) * 4096);
    };
    auto role = [&](int w) { int c; asm volatile("mov.u32 %0, %%ctaid.x;" : "=r"(c)); return c < NGEMM && wg == w; };
    auto extra = [&]() { int c; asm volatile("mov.u32 %0, %%ctaid.x;" : "=r"(c)); return c >= NGEMM; };
    if (wg == 1) {
    if (role(1)) {
      asm volatile("setmaxnreg.inc.sync.aligned.u32 224;");
      float d0[96], dw[96];
      float r0 = 0.f, r1 = 0.f, r2 = 0.f, r3 = 0.f;
      asm volatile("cp.async.wait_all;" ::: "memory");
      asm volatile("fence.proxy.async.shared::cta;" ::: "memory");
      bar_arrive<2, 256>();
      {
        const int col = p < 96 ? nt * 96 + p : 768 + (nt >> 2) * 32 + (p - 96);
        const uint32_t bb = __ldg(reinterpret_cast<const uint32_t*>(b1) + col), ww = __ldg(reinterpret_cast<const uint32_t*>(w2) + col);
        reinterpret_cast<float4*>(smem + OFF_EPI)[p] =
            make_float4(ALPHA * bf_lo(bb), ALPHA * bf_hi(bb), (0.5f / ALPHA) * bf_lo(ww), (0.5f / ALPHA) * bf_hi(ww));
      }
      mbar_wait(bars + 8 * BAR_W0, 0);
      mbar_wait(bars + 8 * BAR_FULL, 0);
      wg_fence();
#pragma unroll
      for (int k = 0; k < 4; k++) {
        wgmma_ss_n192(d0, desc_x(U_XB) + 2 * k, desc_w(U_W) + 128 * k, k != 0);
        wgmma_ss_n192(dw, desc_x(U_XB + 1) + 2 * k, desc_w(U_W) + 128 * k, k != 0);
      }
      wg_commit();
      int s = 1;
#pragma unroll 1
      for (int f = 1; f < FS; f++) {
        mbar_wait(full_bar(bars, f), 0);
        const uint64_t dA = desc_x(U_XB + 2 * s), dB = desc_w(U_W + 4 * s);
        wg_fence();
        wgmma_ss_n192(d0, dA, dB, 1);
        wgmma_ss_n192(dw, dA + 512, dB, 1);
        wg_commit();
        wg_wait<1>();
        if (p < 2) mbar_arrive_cta(ev_bar(bars, f - 1), p);
#pragma unroll
        for (int k = 1; k < 4; k++) {
          wgmma_ss_n192(d0, dA + 2 * k, dB + 128 * k, 1);
          wgmma_ss_n192(dw, dA + 512 + 2 * k, dB + 128 * k, 1);
        }
        wg_commit();
        if (++s == 3) s = 0;
      }
      wg_wait<0>();
      if (p < 2) mbar_arrive_cta(ev_bar(bars, FS - 1), p);
      {
        const uint32_t a = sb + OFF_GIDX + 64 * NF * 4;
        int v[4];
#pragma unroll
        for (int i = 0; i < 4; i++) v[i] = lds32(a + (((p & 15) * 4 + i) * NF + (NF - 1 - (p >> 4))) * 4);
        const int2 w = lds64(sb + OFF_GIDX + (((nt >> 2) * 32 + (p >> 2)) * NF + FS + (p & 3) * 2) * 4);
        asm volatile("st.shared.v2.b32 [%0], {%1, %2};" ::"r"(sb + OFF_CIDX + p * 8), "r"(w.x), "r"(w.y) : "memory");
        bar_sync<3, 128>();
        asm volatile("st.shared.v4.b32 [%0], {%1, %2, %3, %4};" ::"r"(sb + OFF_TIDX + p * 16), "r"(v[0]), "r"(v[1]), "r"(v[2]), "r"(v[3]) : "memory");
        bar_sync<3, 128>();
        if (p < 2) {
          const unsigned epoch = gp.s->epoch[cta] + 1;
          flag_wait(&gp.s->foldflag, epoch * NEXTRA * 8, 0);
          sts32f(bars + 8 * BAR_EPOCH, __uint_as_float(epoch));
          mbar_arrive(bars + 8 * BAR_T);
        }
        __syncwarp();
      }
      mbar_wait(full_bar(bars, NF), 0);
      bar_sync<4, 256>();
#pragma unroll
      for (int t = 0; t < 4; t++) {
        if (t) mbar_wait(full_bar(bars, NF + t), 0);
        const uint64_t dA = desc_x(b_x(t)), dB = desc_w(b_w(t), b_ws(t));
        wg_fence();
#pragma unroll
        for (int k = 0; k < 4; k++) {
          wgmma_ss_n192(d0, dA + 2 * k, dB + 128 * k, 1);
          wgmma_ss_n192(dw, dA + 512 + 2 * k, dB + 128 * k, 1);
          if (k == 1 && t) {
            wg_commit();
            wg_wait<1>();
            wg_fence();
          }
        }
        wg_commit();
        if (t) {
          if (t == 1) mbar_wait(ev_bar(bars, NF - 1), 0);
          load_w(3 + t);
          if (t == 1 && p < 4) mbar_arrive_cta(ev_bar(bars, 26), p & 1);
        }
      }
      mbar_wait(full_bar(bars, NF + 4), 0);
      tile_step(d0, desc_x(b_x(4)), desc_w(b_w(4)));
      wg_wait<1>();
      load_w(7);
      if (p < 4) mbar_arrive(ev_bar(bars, EV_CW));
      mbar_wait(full_bar(bars, NF + 5), 0);
      tile_step(d0, desc_x(b_x(5)), desc_w(b_w(5)));
      mbar_wait(full_bar(bars, NF + 6), 0);
      tile_step(d0, desc_x(b_x(6)), desc_w(b_w(6)));
      mbar_wait(full_bar(bars, NF + 7), 0);
      tile_step(d0, desc_x(b_x(7)), desc_w(b_w(7), 4));
      tile_step(dw, desc_x(b_x(4) + 1), desc_w(b_w(4)));
      Gelu<24> g0;
      g0.start<24 - PS - PS2>(ep);
      wg_wait<1>();
      tile_step(dw, desc_x(b_x(5) + 1), desc_w(b_w(5)));
      g0.part<24 - PS - PS2, 24 - PS2>(d0, r0, r1);
      pin(r0, r1, ep, gp.zero);
      wg_wait<1>();
      if (p < 4) mbar_arrive(ev_bar(bars, EV_SLOT));
      tile_step(dw, desc_x(b_x(6) + 1), desc_w(b_w(6)));
      g0.part<24 - PS2, 24>(d0, r0, r1);
      pin(r0, r1, ep, gp.zero);
      wg_wait<1>();
      tile_step(dw, desc_x(b_x(7) + 1), desc_w(b_w(7), 4));
      gelu_slow<24 - PS - PS2 - PX, 24 - PS - PS2>(d0, r0, r1, ep, gp.zero);
      wg_wait<0>();
      asm volatile("setmaxnreg.dec.sync.aligned.u32 %0;" ::"n"(RC));
      mbar_wait(bars + 8 * BAR_X0, 0);
      asm volatile("fence.proxy.async.global;" ::: "memory");
#pragma unroll 1
      for (int n = 7 + (warp & 3); n < 17; n += 4) cin_job(sb, fresh(cta), n, &tmC, &tmT);
      gelu_slow<0, 24 - PS - PS2 - PX>(d0, r0, r1, ep, gp.zero);
      gelu_slow<0, 24>(dw, r2, r3, ep, gp.zero);
      mbar_wait(bars + 8 * BAR_RS0, 0);
      const float4 w = lds128f(sb + OFF_RS0 + p * 16);
      const unsigned epoch = lds32(bars + 8 * BAR_EPOCH);
      uint2* dst = gp.s->part + (nt * NB + (cta >> 3) * 256 + (warp & 3) * 16);
      const uint32_t o = (lane & 1) * 8 + (lane & 2) * 32 + (lane >> 2);
      put_tagged(dst + (o ^ ((cta & 2) * 64 + (~cta & 1) * 64)), quad_sum(w.x, w.y, w.z, w.w, lane), epoch);
      put_tagged(dst + (o ^ ((~cta & 2) * 64)), quad_sum(r0, r1, r2, r3, lane), epoch);
    }
    if (extra()) {
      const int w = warp & 3;
#pragma unroll 1
      for (int t = w >> 1; t < NPAIR; t += 2) {
        const uint32_t cb = sb + XOFF_BAR + ((w & 1) * 2 * NPAIR + t) * 8;
        if (t >= 4) mbar_wait(cb + 8 * (NPAIR - 4), 0);
        row_job(sb + XOFF_SLOT + ((w & 1) * 8 + (t & 3) * 2) * XSLOT, sb + XOFF_CIDX + ((w & 1) * (NC_EXTRA / 2) + 2 * t + 1) * NF * 4,
                t == NPAIR - 1 ? 1 : 2, cb, &tmT);
      }
    }
    if (warp == 7 || extra()) {
      int cta; asm volatile("mov.u32 %0, %%ctaid.x;" : "=r"(cta));
      const unsigned epoch = lds32(bars + 8 * BAR_EPOCH);
      float s = (sb & 0xFFFFFF) == SMEM_BASE ? bf2f(bout[0]) : __int_as_float(0x7fc00000);
      const int r = cta < NGEMM ? lane : (warp & 3) * (NC_EXTRA / 4) + min(lane, NC_EXTRA / 4 - 1), row = cin_row(cta, r);
      const uint2* src = gp.s->part + row;
      uint2 v[8];
#pragma unroll 1
      for (int i = 0; i < 100000; i++) {
        unsigned miss = 0;
#pragma unroll
        for (int n = 0; n < 8; n++)
          asm volatile("ld.relaxed.gpu.global.v2.b32 {%0, %1}, [%2];" : "=r"(v[n].x), "=r"(v[n].y) : "l"(src + n * NB) : "memory");
#pragma unroll
        for (int n = 0; n < 8; n++) miss |= v[n].y ^ epoch;
        if (__all_sync(0xffffffffu, miss == 0)) break;
        __nanosleep(POLL);
      }
#pragma unroll
      for (int n = 0; n < 8; n++) s += __uint_as_float(v[n].x);
      sts64f(sb + OFF_DNN + r * 8, s, __int_as_float(row));
      __syncwarp();
      if (lane == 0) mbar_arrive(bars + 8 * BAR_DNN);
      if (warp == 7 && lane == 0) gp.s->epoch[cta] = epoch;
    }
    return;
    }
    if (role(0)) {
      asm volatile("setmaxnreg.inc.sync.aligned.u32 256;");
      float d0[96], dx[32], dw[96];
      float r0 = 0.f, r1 = 0.f, r2 = 0.f, r3 = 0.f;
      Gelu<24> g0;
      mbar_wait(bars + 8 * BAR_W0, 0);
      asm volatile("cp.async.wait_all;" ::: "memory");
      asm volatile("fence.proxy.async.shared::cta;" ::: "memory");
      bar_sync<2, 256>();
      const uint64_t dA0 = desc_x(rank), dA1 = desc_x(rank ^ 1);
      wg_fence();
#pragma unroll
      for (int k = 0; k < 4; k++) {
        wgmma_ss_n256(dw, dx, dA0 + 2 * k, desc_w(U_W) + 128 * k, k != 0);
        wgmma_ss_n192(d0, dA1 + 2 * k, desc_w(U_W) + 128 * k, k != 0);
      }
      wg_commit();
      keep_x(0, 0);
#pragma unroll 1
      for (int f = 1; f < NF - 3; f++) {
        mbar_wait(full_bar(bars, f), 0);
        const int st = (STAGES >> (2 * f)) & 3, xo = (st == 3 ? U_SP : 2 * st) * (UNIT / 16);
        const uint64_t dB = desc_w(U_W + 4 * st);
        wg_fence();
        wgmma_ss_n256(dw, dx, dA0 + xo, dB, 1);
        wgmma_ss_n192(d0, dA1 + xo, dB, 1);
        wg_commit();
        store_read<0>();
        wg_wait<1>();
        if (p < (f > FS ? 4 : 2)) mbar_arrive_cta(ev_bar(bars, f - 1), p & 1);
#pragma unroll
        for (int k = 1; k < 4; k++) {
          wgmma_ss_n256(dw, dx, dA0 + xo + 2 * k, dB + 128 * k, 1);
          wgmma_ss_n192(d0, dA1 + xo + 2 * k, dB + 128 * k, 1);
        }
        wg_commit();
        if (f < FS) keep_x(f, 2 * st);
      }
      {
        constexpr int x3 = 2 * (UNIT / 16), x4 = U_SP * (UNIT / 16), x5 = 4 * (UNIT / 16);
        const uint64_t dB3 = desc_w(U_W + 4), dB4 = desc_w(U_W + 12), dB5 = desc_w(U_W + 8);
        mbar_wait(full_bar(bars, NF - 3), 0);
        tile_step(d0, dA1 + x3, dB3);
        wg_wait<1>();
        if (p < 4) mbar_arrive_cta(ev_bar(bars, NF - 4), p & 1);
        mbar_wait(full_bar(bars, NF - 2), 0);
        tile_step(d0, dA1 + x4, dB4);
        mbar_wait(full_bar(bars, NF - 1), 0);
        tile_step(d0, dA1 + x5, dB5);
        wide_step(dw, dx, dA0 + x3, dB3);
        g0.start(ep);
        wg_wait<1>();
        wide_step(dw, dx, dA0 + x4, dB4);
        g0.part<0, PE1>(d0, r0, r1, bars + 8 * BAR_W0);
        pin(r0, r1, ep, gp.zero);
        wg_wait<1>();
        if (p < 4) mbar_arrive_cta(ev_bar(bars, NF - 3), p & 1);
        wide_step<0, HK>(dw, dx, dA0 + x5, dB5);
        g0.part<PE1, PE2>(d0, r0, r1, bars + 8 * BAR_W0);
        pin(r0, r1, ep, gp.zero);
        wg_wait<1>();
        bar_arrive<4, 256>();
        if (p < 4) mbar_arrive_cta(ev_bar(bars, NF - 2), p & 1);
        wide_step<HK, 4>(dw, dx, dA0 + x5, dB5);
        g0.part<PE2, PE0>(d0, r0, r1);
        pin(r0, r1, ep, gp.zero);
        wg_wait<0>();
        load_w(3);
        if (p < 4) mbar_arrive_cta(ev_bar(bars, NF - 1), p & 1);
        asm volatile("cp.async.bulk.wait_group 0;" ::: "memory");
        if (warp == 0 && elect1()) mbar_arrive(bars + 8 * BAR_X0);
      }
      g0.part<PE0, 24>(d0, r0, r1);
      Gelu<8> gx;
      gx.start(ep + 24 * 64);
      gx.part<0, 8>(dx, r2, r3);
      float d1[96];
      hand_on(d1, dw);
      asm volatile("setmaxnreg.dec.sync.aligned.u32 %0;" ::"n"(RC));
      Gelu<24> g1;
      g1.start(ep);
      g1.part<0, 24>(d1, r2, r3);
      mbar_wait(ev_bar(bars, EV_CW), 0);
      sts128f(sb + OFF_RS0 + p * 16, r0, r1, r2, r3);
      __syncwarp();
      if (lane == 0) mbar_arrive(bars + 8 * BAR_RS0);
    }
  }

    {
    int cta, tid;
    asm volatile("mov.u32 %0, %%ctaid.x;" : "=r"(cta));
    asm volatile("mov.u32 %0, %%tid.x;" : "=r"(tid));
    cta = __shfl_sync(0xffffffffu, cta, 0);
    const bool gemm = cta < NGEMM;
    const int p = tid & 127, wg = __shfl_sync(0xffffffffu, tid >> 8, 0);
    CinCtx c;
    float accA[28];
    uint32_t xA[10][2], z[8];
    cin_begin(c, sb, wg, gemm && wg ? slot_of(1, 0) : OFF_GIDX + wg * XSLOT, xA, accA, z);
    const int ncin = cin_count(cta);
    const int n0 = gemm ? NC_WG0 : NC_EXTRA / 2;
    const int rb = wg ? n0 : 0;
    const int nj = wg ? ncin - n0 : n0;
    cin_setup(c, sb, wg, p, gemm, nj, gp.zero);
    uint32_t fa = sb + (gemm ? slot_of(wg, (p >> 3) + 1) + NF * 128 : (wg ? XOFF_CIN1 : XOFF_CIN0) + (p >> 3) * CROW) + (p & 7) * 16, fd = sb + OFF_DNN + rb * 8;
    asm volatile("" : "+r"(fa), "+r"(fd));
    auto wg_sync = [&]() { if (wg == 0) bar_sync<1, 128>(); else bar_sync<6, 128>(); };
    mbar_wait(gemm ? bars + 8 * BAR_GDONE : ev_bar(bars, EV_END), 0);
    cin_run(c, nj, xA, accA, z, [&]() {
      mbar_wait(bars + 8 * BAR_DNN, 0);
    }, [&](int j) {
    });
    int2 dn = lds64(fd + (p >> 3) * 8);
    __nv_bfloat16* op = out + dn.y;
    float d = (p & 7) == 0 ? __int_as_float(dn.x) : 0.f;
    asm volatile("" : "+f"(d), "+l"(op));
    wg_sync();
#pragma unroll 1
    for (int r = 0;;) {
      const float4 v0 = lds128f(fa), v1 = lds128f(fa + 128), v2 = lds128f(fa + 256), v3 = lds128f(fa + 384);
      float s = (((v0.x + v0.y) + (v0.z + v0.w)) + ((v1.x + v1.y) + (v1.z + v1.w))) +
                (((v2.x + v2.y) + (v2.z + v2.w)) + (((v3.x + v3.y) + d) + (v3.z + v3.w)));
      s += __shfl_xor_sync(0xffffffffu, s, 1);
      s += __shfl_xor_sync(0xffffffffu, s, 2);
      s += __shfl_xor_sync(0xffffffffu, s, 4);
      if ((p & 7) == 0 && r + (p >> 3) < nj) *op = __float2bfloat16(s);
      r += 16;
      if (r >= nj) break;
      fa += 16 * CROW;
      dn = lds64(fd + (r + (p >> 3)) * 8);
      op = out + dn.y;
      d = (p & 7) == 0 ? __int_as_float(dn.x) : 0.f;
    }
    }
}

typedef CUresult (*EncodeFn)(CUtensorMap*, CUtensorMapDataType, cuuint32_t, void*, const cuuint64_t*, const cuuint64_t*,
                             const cuuint32_t*, const cuuint32_t*, CUtensorMapInterleave, CUtensorMapSwizzle,
                             CUtensorMapL2promotion, CUtensorMapFloatOOBfill);

extern "C" void kernel_launch(void* const* d_in, const int* in_sizes, int n_in, void* d_out, int out_size) {
  void* fn = nullptr;
  cudaDriverEntryPointQueryResult q;
  cudaGetDriverEntryPoint("cuTensorMapEncodeTiled", &fn, cudaEnableDefault, &q);
  EncodeFn enc = (EncodeFn)fn;
  CUtensorMap tmW, tmT, tmS, tmC;
  const cuuint32_t es[3] = {1, 1, 1};
  {
    cuuint64_t dims[2] = {DIN, DIN}, st[1] = {DIN * 2};
    cuuint32_t box[2] = {64, 64};
    enc(&tmW, CU_TENSOR_MAP_DATA_TYPE_BFLOAT16, 2, d_in[4], dims, st, box, es, CU_TENSOR_MAP_INTERLEAVE_NONE,
        CU_TENSOR_MAP_SWIZZLE_128B, CU_TENSOR_MAP_L2_PROMOTION_NONE, CU_TENSOR_MAP_FLOAT_OOB_FILL_NONE);
  }
  {
    cuuint64_t dims[2] = {64, (cuuint64_t)(in_sizes[1] / 64)}, st[1] = {128};
    cuuint32_t box[2] = {64, 1};
    enc(&tmT, CU_TENSOR_MAP_DATA_TYPE_BFLOAT16, 2, d_in[1], dims, st, box, es, CU_TENSOR_MAP_INTERLEAVE_NONE,
        CU_TENSOR_MAP_SWIZZLE_128B, CU_TENSOR_MAP_L2_PROMOTION_NONE, CU_TENSOR_MAP_FLOAT_OOB_FILL_NONE);
  }
  void* x0 = nullptr;
  cudaGetSymbolAddress(&x0, g_x0);
  {
    cuuint64_t dims[2] = {FS * 64, NB}, st[1] = {FS * 128};
    cuuint32_t box[2] = {64, NC_GEMM + 1};
    enc(&tmS, CU_TENSOR_MAP_DATA_TYPE_BFLOAT16, 2, x0, dims, st, box, es, CU_TENSOR_MAP_INTERLEAVE_NONE,
        CU_TENSOR_MAP_SWIZZLE_128B, CU_TENSOR_MAP_L2_PROMOTION_NONE, CU_TENSOR_MAP_FLOAT_OOB_FILL_NONE);
  }
  {
    cuuint64_t dims[2] = {64, NB * FS}, st[1] = {128};
    cuuint32_t box[2] = {64, FS};
    enc(&tmC, CU_TENSOR_MAP_DATA_TYPE_BFLOAT16, 2, x0, dims, st, box, es, CU_TENSOR_MAP_INTERLEAVE_NONE,
        CU_TENSOR_MAP_SWIZZLE_128B, CU_TENSOR_MAP_L2_PROMOTION_NONE, CU_TENSOR_MAP_FLOAT_OOB_FILL_NONE);
  }
  GPtr gp;
  gp.zero = 0;
  cudaGetSymbolAddress((void**)&gp.s, g_scratch);
  cudaGetSymbolAddress((void**)&gp.tab, g_slot_tab);
  cudaFuncSetAttribute(xdeepfm_kernel, cudaFuncAttributeMaxDynamicSharedMemorySize, SMEM_BYTES);
  xdeepfm_kernel<<<GRID, 384, SMEM_BYTES, cudaStreamPerThread>>>(
      (const int*)d_in[0], (const __nv_bfloat16*)d_in[1], (const __nv_bfloat16*)d_in[4], (const __nv_bfloat16*)d_in[5],
      (const __nv_bfloat16*)d_in[6], (const __nv_bfloat16*)d_in[2], (const __nv_bfloat16*)d_in[3],
      (const __nv_bfloat16*)d_in[7], (__nv_bfloat16*)d_out, gp, tmW, tmT, tmS, tmC);
}
```
